```python
import torch

def _softmax(x, axis=-1):
    return torch.softmax(x, dim=axis)
def _gelu(x):
    return torch.nn.functional.gelu(x, approximate="tanh")
def _silu(x):
    return torch.nn.functional.silu(x)
def _sigmoid(x):
    return torch.sigmoid(x)
def _layernorm(x, axis=-1, eps=1e-5):
    m = x.mean(dim=axis, keepdim=True)
    v = x.var(dim=axis, keepdim=True, unbiased=False)
    return (x - m) / torch.sqrt(v + eps)
def _scatter_add(tgt, idx, src, axis=0):
    return tgt.clone().index_add_(axis, idx, src)
def _segment_sum(src, seg, n):
    out = torch.zeros((n,) + src.shape[1:], dtype=src.dtype)
    return out.index_add_(0, seg, src)
def _pad(x, pw):
    flat = tuple(v for pair in reversed(pw) for v in pair)
    return torch.nn.functional.pad(x, flat)

kernel_name = 'sequential_preLN__mha_block__dense_activation_relu__prompt'

def setup_inputs():

    _w = (lambda a: (lambda t: t.to(torch.bfloat16) if t.is_floating_point() else t)(torch.as_tensor(a)))
    def _A_setup():
        B, S, D, H = 1, 2048, 576, 32
        return {
            "x": _w((lambda *s: torch.randn(*s, dtype=torch.bfloat16) * 0.05)(B, S, D)),
            "wqkv": _w((lambda *s: torch.randn(*s, dtype=torch.bfloat16) * 0.05)(D, 3 * D)),
            "wo": _w((lambda *s: torch.randn(*s, dtype=torch.bfloat16) * 0.05)(D, D)),
        }
    _A_in = _A_setup()

    def _B_setup():
        B, S, D, Dff = 1, 2048, 576, 4608
        return {
            "x": _w((lambda *s: torch.randn(*s, dtype=torch.bfloat16) * 0.05)(B, S, D)),
            "w1": _w((lambda *s: torch.randn(*s, dtype=torch.bfloat16) * 0.05)(D, Dff)),
            "w2": _w((lambda *s: torch.randn(*s, dtype=torch.bfloat16) * 0.05)(Dff, D)),
        }
    _B_in = _B_setup()

    return {
        "A_x": _A_in["x"],
        "A_wqkv": _A_in["wqkv"],
        "A_wo": _A_in["wo"],
        "B_x": _B_in["x"],
        "B_w1": _B_in["w1"],
        "B_w2": _B_in["w2"],
    }

def reference(A_x, A_wqkv, A_wo, B_x, B_w1, B_w2):
    def _A_ref(x, wqkv, wo):
        B, S, D = x.shape
        H = 32
        Dh = D // H
        qkv = (lambda x, *d: x.permute(*d))((x @ wqkv).reshape(B, S, 3, H, Dh), 2, 0, 3, 1, 4)
        q, k, v = qkv[0], qkv[1], qkv[2]
        scores = torch.einsum("bhqd,bhkd->bhqk", q, k) * (Dh ** -0.5)
        p = _softmax(scores, axis=-1)
        o = torch.einsum("bhqk,bhkd->bhqd", p, v)
        return (lambda x, *d: x.permute(*d))(o, 0, 2, 1, 3).reshape(B, S, D) @ wo

    def _B_ref(x, w1, w2):
        h = torch.einsum("bsd,df->bsf", x, w1)
        zero = torch.zeros_like(h)
        h = torch.maximum(h, zero)
        return torch.einsum("bsf,fd->bsd", h, w2)

    x = A_x
    h = x + _A_ref(_layernorm(x, axis=-1), A_wqkv, A_wo)
    h2 = h + _B_ref(_layernorm(h, axis=-1), B_w1, B_w2)
    return h2
```

```cpp
#include <cuda_runtime.h>
#include <cuda_bf16.h>
#include <cuda.h>
#include <stdint.h>

namespace {

constexpr int SEQ = 2048, DM = 576, FF = 4608;
constexpr float LN_EPS = 1e-5f;
constexpr float QSCALE = 0.34004428f;

constexpr int BLK_BYTES = 6144;
constexpr int SLOT_BYTES = 16 * BLK_BYTES;
constexpr uint32_t POLY_PATTERN = 0xB5B5u;

__device__ __align__(1024) uint8_t g_qkv[96 * SLOT_BYTES];
__device__ __align__(1024) __nv_bfloat16 g_attn[SEQ * DM];
__device__ __align__(1024) __nv_bfloat16 g_h[SEQ * DM];
__device__ __align__(1024) uint8_t g_wo_img[8 * 82944];
__device__ __align__(1024) uint8_t g_part[16 * 9 * 8 * 16384];
__device__ __align__(16) float g_cs0[1728 + 16];
__device__ __align__(16) float g_cs1[FF];
__device__ __align__(16) float2 g_xstat[SEQ];
__device__ __align__(16) float2 g_hstat[SEQ * 8];
__device__ __align__(16) float g_kmax[8 * 128];
__device__ unsigned int g_cnt_a[32];
__device__ unsigned int g_flag_c[16 + 16 * 9 * 8];

constexpr uint32_t SPIN_LIMIT = 1u << 18;

__device__ __forceinline__ uint32_t smem_u32(const void* p) { return (uint32_t)__cvta_generic_to_shared(p); }
__device__ __forceinline__ void mbar_init(uint32_t bar, uint32_t cnt) { asm volatile("mbarrier.init.shared::cta.b64 [%0], %1;" :: "r"(bar), "r"(cnt) : "memory"); }
__device__ __forceinline__ void mbar_expect(uint32_t bar, uint32_t bytes) { asm volatile("mbarrier.arrive.expect_tx.shared::cta.b64 _, [%0], %1;" :: "r"(bar), "r"(bytes) : "memory"); }
__device__ __forceinline__ void mbar_arrive(uint32_t bar) { asm volatile("mbarrier.arrive.shared::cta.b64 _, [%0];" :: "r"(bar) : "memory"); }
__device__ __forceinline__ void mbar_arrive_cluster(uint32_t bar) { asm volatile("mbarrier.arrive.release.cluster.shared::cluster.b64 _, [%0];" :: "r"(bar) : "memory"); }
__device__ __forceinline__ bool mbar_try(uint32_t bar, uint32_t parity) {
    uint32_t ok;
    asm volatile("{\n.reg .pred p;\nmbarrier.try_wait.parity.shared::cta.b64 p, [%1], %2;\nselp.u32 %0, 1, 0, p;\n}\n" : "=r"(ok) : "r"(bar), "r"(parity) : "memory");
    return ok;
}
__device__ __forceinline__ void mbar_wait(uint32_t bar, uint32_t parity) {
    if (mbar_try(bar, parity)) return;
    for (uint32_t i = 0; !mbar_try(bar, parity); i++) if (i > SPIN_LIMIT) break;
}
__device__ __forceinline__ bool mbar_try_cluster(uint32_t bar, uint32_t parity) {
    uint32_t ok;
    asm volatile("{\n.reg .pred p;\nmbarrier.try_wait.parity.acquire.cluster.shared::cta.b64 p, [%1], %2;\nselp.u32 %0, 1, 0, p;\n}\n" : "=r"(ok) : "r"(bar), "r"(parity) : "memory");
    return ok;
}
__device__ __forceinline__ void mbar_wait_cluster(uint32_t bar, uint32_t parity) {
    for (uint32_t i = 0; !mbar_try_cluster(bar, parity); i++) if (i > SPIN_LIMIT) __trap();
}
__device__ __forceinline__ uint32_t mapa(uint32_t addr, uint32_t rank) { uint32_t r; asm("mapa.shared::cluster.u32 %0, %1, %2;" : "=r"(r) : "r"(addr), "r"(rank)); return r; }
__device__ __forceinline__ void cluster_sync() { asm volatile("barrier.cluster.arrive.release.aligned;\nbarrier.cluster.wait.acquire.aligned;" ::: "memory"); }
__device__ __forceinline__ void fence_mbar_init() { asm volatile("fence.mbarrier_init.release.cluster;" ::: "memory"); }
__device__ __forceinline__ void fence_async_smem() { asm volatile("fence.proxy.async.shared::cta;" ::: "memory"); }
__device__ __forceinline__ void fence_async_all() { asm volatile("fence.proxy.async;" ::: "memory"); }
__device__ __forceinline__ void fence_gpu() { asm volatile("fence.acq_rel.gpu;" ::: "memory"); }
__device__ __forceinline__ void nbar_sync(uint32_t id, uint32_t n) { asm volatile("bar.sync %0, %1;" :: "r"(id), "r"(n) : "memory"); }
__device__ __forceinline__ void nbar_arrive(uint32_t id, uint32_t n) { asm volatile("bar.arrive %0, %1;" :: "r"(id), "r"(n) : "memory"); }
__device__ __forceinline__ void pdl_wait() { asm volatile("griddepcontrol.wait;" ::: "memory"); }
__device__ __forceinline__ void pdl_launch() { asm volatile("griddepcontrol.launch_dependents;" ::: "memory"); }
__device__ __forceinline__ void flag_add(unsigned int* p) { asm volatile("red.release.gpu.global.add.u32 [%0], 1;" :: "l"(p) : "memory"); }
__device__ __forceinline__ void flag_wait(const unsigned int* p, uint32_t target) {
    uint32_t v;
    for (uint32_t i = 0;; i++) {
        asm volatile("ld.acquire.gpu.global.u32 %0, [%1];" : "=r"(v) : "l"(p) : "memory");
        if (v >= target) break;
        if (i > SPIN_LIMIT) __trap();
    }
}
__device__ __forceinline__ void bulk_load(uint32_t dst, const void* src, uint32_t bytes, uint32_t bar) {
    asm volatile("cp.async.bulk.shared::cluster.global.mbarrier::complete_tx::bytes [%0], [%1], %2, [%3];" :: "r"(dst), "l"(src), "r"(bytes), "r"(bar) : "memory");
}
__device__ __forceinline__ void bulk_store(void* dst, uint32_t src, uint32_t bytes) {
    asm volatile("cp.async.bulk.global.shared::cta.bulk_group [%0], [%1], %2;" :: "l"(dst), "r"(src), "r"(bytes) : "memory");
}
__device__ __forceinline__ void bulk_commit() { asm volatile("cp.async.bulk.commit_group;" ::: "memory"); }
__device__ __forceinline__ void bulk_wait_read() { asm volatile("cp.async.bulk.wait_group.read 0;" ::: "memory"); }
__device__ __forceinline__ void l2_prefetch(const void* src, uint32_t bytes) { asm volatile("cp.async.bulk.prefetch.L2.global [%0], %1;" :: "l"(src), "r"(bytes) : "memory"); }
__device__ __forceinline__ void tma_2d(uint32_t dst, const CUtensorMap* m, int c0, int c1, uint32_t bar) {
    asm volatile("cp.async.bulk.tensor.2d.shared::cluster.global.mbarrier::complete_tx::bytes [%0], [%1, {%3, %4}], [%2];"
                 :: "r"(dst), "l"(m), "r"(bar), "r"(c0), "r"(c1) : "memory");
}
__device__ __forceinline__ void tma_2d_mc(uint32_t dst, const CUtensorMap* m, int c0, int c1, uint32_t bar) {
    asm volatile("cp.async.bulk.tensor.2d.shared::cluster.global.mbarrier::complete_tx::bytes.multicast::cluster [%0], [%1, {%3, %4}], [%2], %5;"
                 :: "r"(dst), "l"(m), "r"(bar), "r"(c0), "r"(c1), "h"((uint16_t)3) : "memory");
}
__device__ __forceinline__ void tma_3d_mc(uint32_t dst, const CUtensorMap* m, int c0, int c1, uint32_t bar) {
    asm volatile("cp.async.bulk.tensor.3d.shared::cluster.global.mbarrier::complete_tx::bytes.multicast::cluster [%0], [%1, {%3, %4, %5}], [%2], %6;"
                 :: "r"(dst), "l"(m), "r"(bar), "r"(c0), "r"(c1), "r"(0), "h"((uint16_t)3) : "memory");
}
__device__ __forceinline__ void tma_store_2d(const CUtensorMap* m, uint32_t src, int c0, int c1) {
    asm volatile("cp.async.bulk.tensor.2d.global.shared::cta.bulk_group [%0, {%2, %3}], [%1];" :: "l"(m), "r"(src), "r"(c0), "r"(c1) : "memory");
}
__device__ __forceinline__ void tma_prefetch_desc(const CUtensorMap* m) { asm volatile("prefetch.tensormap [%0];" :: "l"(m) : "memory"); }
__device__ __forceinline__ void wg_fence() { asm volatile("wgmma.fence.sync.aligned;" ::: "memory"); }
__device__ __forceinline__ void wg_commit() { asm volatile("wgmma.commit_group.sync.aligned;" ::: "memory"); }
template <int N> __device__ __forceinline__ void wg_wait() { asm volatile("wgmma.wait_group.sync.aligned %0;" :: "n"(N) : "memory"); }
template <int N> __device__ __forceinline__ void fence_regs(float (&d)[N]) {
#pragma unroll
    for (int i = 0; i < N; i++) asm volatile("" : "+f"(d[i]) :: "memory");
}
template <int N> __device__ __forceinline__ void fence_regs(uint32_t (&d)[N]) {
#pragma unroll
    for (int i = 0; i < N; i++) asm volatile("" : "+r"(d[i]) :: "memory");
}
__device__ __forceinline__ uint32_t pack_bf16(float lo, float hi) { uint32_t r; asm("cvt.rn.bf16x2.f32 %0, %1, %2;" : "=r"(r) : "f"(hi), "f"(lo)); return r; }
__device__ __forceinline__ uint32_t pack_bf16_relu(float lo, float hi) { uint32_t r; asm("cvt.rn.relu.bf16x2.f32 %0, %1, %2;" : "=r"(r) : "f"(hi), "f"(lo)); return r; }
__device__ __forceinline__ float bf_lo(uint32_t w) { return __uint_as_float(w << 16); }
__device__ __forceinline__ float bf_hi(uint32_t w) { return __uint_as_float(w & 0xFFFF0000u); }
__device__ __forceinline__ float ex2(float x) { float r; asm("ex2.approx.ftz.f32 %0, %1;" : "=f"(r) : "f"(x)); return r; }
__device__ __forceinline__ void sts32(uint32_t a, uint32_t v) { asm volatile("st.shared.b32 [%0], %1;" :: "r"(a), "r"(v) : "memory"); }
__device__ __forceinline__ void sts128(uint32_t a, uint32_t x, uint32_t y, uint32_t z, uint32_t w) { asm volatile("st.shared.v4.b32 [%0], {%1, %2, %3, %4};" :: "r"(a), "r"(x), "r"(y), "r"(z), "r"(w) : "memory"); }
__device__ __forceinline__ uint32_t lds32(uint32_t a) { uint32_t v; asm volatile("ld.shared.b32 %0, [%1];" : "=r"(v) : "r"(a) : "memory"); return v; }
__device__ __forceinline__ float2 lds64f(uint32_t a) { float2 v; asm volatile("ld.shared.v2.f32 {%0, %1}, [%2];" : "=f"(v.x), "=f"(v.y) : "r"(a) : "memory"); return v; }
__device__ __forceinline__ uint4 lds128(uint32_t a) { uint4 v; asm volatile("ld.shared.v4.b32 {%0, %1, %2, %3}, [%4];" : "=r"(v.x), "=r"(v.y), "=r"(v.z), "=r"(v.w) : "r"(a) : "memory"); return v; }

__device__ __forceinline__ uint32_t desc_addr(uint32_t a) { return (a & 0x3FFFFu) >> 4; }
constexpr uint32_t HI_SW128 = (1024 >> 4) | (1u << 30);
constexpr uint32_t HI_SW64 = (512 >> 4) | (2u << 30);

__device__ __forceinline__ void mma_ss_n224(float (&d)[112], uint32_t alo, uint32_t ahi, uint32_t blo, uint32_t bhi, uint32_t acc) {
    asm volatile("{\n.reg .b64 da, db;\n.reg .pred p;\nsetp.ne.u32 p, %116, 0;\nmov.b64 da, {%112, %113};\nmov.b64 db, {%114, %115};\n"
        "wgmma.mma_async.sync.aligned.m64n224k16.f32.bf16.bf16 "
        "{%0, %1, %2, %3, %4, %5, %6, %7, %8, %9, %10, %11, %12, %13, %14, %15, "
        "%16, %17, %18, %19, %20, %21, %22, %23, %24, %25, %26, %27, %28, %29, %30, %31, "
        "%32, %33, %34, %35, %36, %37, %38, %39, %40, %41, %42, %43, %44, %45, %46, %47, "
        "%48, %49, %50, %51, %52, %53, %54, %55, %56, %57, %58, %59, %60, %61, %62, %63, "
        "%64, %65, %66, %67, %68, %69, %70, %71, %72, %73, %74, %75, %76, %77, %78, %79, "
        "%80, %81, %82, %83, %84, %85, %86, %87, %88, %89, %90, %91, %92, %93, %94, %95, "
        "%96, %97, %98, %99, %100, %101, %102, %103, %104, %105, %106, %107, %108, %109, %110, %111}, "
        "da, db, p, 1, 1, 0, 1;\n}\n"
        : "+f"(d[0]), "+f"(d[1]), "+f"(d[2]), "+f"(d[3]), "+f"(d[4]), "+f"(d[5]), "+f"(d[6]), "+f"(d[7]),
          "+f"(d[8]), "+f"(d[9]), "+f"(d[10]), "+f"(d[11]), "+f"(d[12]), "+f"(d[13]), "+f"(d[14]), "+f"(d[15]),
          "+f"(d[16]), "+f"(d[17]), "+f"(d[18]), "+f"(d[19]), "+f"(d[20]), "+f"(d[21]), "+f"(d[22]), "+f"(d[23]),
          "+f"(d[24]), "+f"(d[25]), "+f"(d[26]), "+f"(d[27]), "+f"(d[28]), "+f"(d[29]), "+f"(d[30]), "+f"(d[31]),
          "+f"(d[32]), "+f"(d[33]), "+f"(d[34]), "+f"(d[35]), "+f"(d[36]), "+f"(d[37]), "+f"(d[38]), "+f"(d[39]),
          "+f"(d[40]), "+f"(d[41]), "+f"(d[42]), "+f"(d[43]), "+f"(d[44]), "+f"(d[45]), "+f"(d[46]), "+f"(d[47]),
          "+f"(d[48]), "+f"(d[49]), "+f"(d[50]), "+f"(d[51]), "+f"(d[52]), "+f"(d[53]), "+f"(d[54]), "+f"(d[55]),
          "+f"(d[56]), "+f"(d[57]), "+f"(d[58]), "+f"(d[59]), "+f"(d[60]), "+f"(d[61]), "+f"(d[62]), "+f"(d[63]),
          "+f"(d[64]), "+f"(d[65]), "+f"(d[66]), "+f"(d[67]), "+f"(d[68]), "+f"(d[69]), "+f"(d[70]), "+f"(d[71]),
          "+f"(d[72]), "+f"(d[73]), "+f"(d[74]), "+f"(d[75]), "+f"(d[76]), "+f"(d[77]), "+f"(d[78]), "+f"(d[79]),
          "+f"(d[80]), "+f"(d[81]), "+f"(d[82]), "+f"(d[83]), "+f"(d[84]), "+f"(d[85]), "+f"(d[86]), "+f"(d[87]),
          "+f"(d[88]), "+f"(d[89]), "+f"(d[90]), "+f"(d[91]), "+f"(d[92]), "+f"(d[93]), "+f"(d[94]), "+f"(d[95]),
          "+f"(d[96]), "+f"(d[97]), "+f"(d[98]), "+f"(d[99]), "+f"(d[100]), "+f"(d[101]), "+f"(d[102]), "+f"(d[103]),
          "+f"(d[104]), "+f"(d[105]), "+f"(d[106]), "+f"(d[107]), "+f"(d[108]), "+f"(d[109]), "+f"(d[110]), "+f"(d[111])
        : "r"(alo), "r"(ahi), "r"(blo), "r"(bhi), "r"(acc));
}
__device__ __forceinline__ void mma_qk_first(float (&d)[32], uint32_t a0, uint32_t a1, uint32_t a2, uint32_t a3, uint32_t blo, uint32_t bhi) {
    asm volatile("{\n.reg .b64 da, db;\nmov.b64 db, {%36, %37};\n"
        "wgmma.mma_async.sync.aligned.m64n64k16.f32.bf16.bf16 "
        "{%0, %1, %2, %3, %4, %5, %6, %7, %8, %9, %10, %11, %12, %13, %14, %15, "
        "%16, %17, %18, %19, %20, %21, %22, %23, %24, %25, %26, %27, %28, %29, %30, %31}, "
        "{%32, %33, %34, %35}, db, 0, 1, 1, 0;\n}\n"
        : "=f"(d[0]), "=f"(d[1]), "=f"(d[2]), "=f"(d[3]), "=f"(d[4]), "=f"(d[5]), "=f"(d[6]), "=f"(d[7]),
          "=f"(d[8]), "=f"(d[9]), "=f"(d[10]), "=f"(d[11]), "=f"(d[12]), "=f"(d[13]), "=f"(d[14]), "=f"(d[15]),
          "=f"(d[16]), "=f"(d[17]), "=f"(d[18]), "=f"(d[19]), "=f"(d[20]), "=f"(d[21]), "=f"(d[22]), "=f"(d[23]),
          "=f"(d[24]), "=f"(d[25]), "=f"(d[26]), "=f"(d[27]), "=f"(d[28]), "=f"(d[29]), "=f"(d[30]), "=f"(d[31])
        : "r"(a0), "r"(a1), "r"(a2), "r"(a3), "r"(blo), "r"(bhi));
}
__device__ __forceinline__ void mma_qk_second(float (&d)[32], uint32_t a0, uint32_t a1, uint32_t a2, uint32_t a3, uint32_t blo, uint32_t bhi) {
    asm volatile("{\n.reg .b64 da, db;\nmov.b64 db, {%36, %37};\n"
        "wgmma.mma_async.sync.aligned.m64n64k16.f32.bf16.bf16 "
        "{%0, %1, %2, %3, %4, %5, %6, %7, %8, %9, %10, %11, %12, %13, %14, %15, "
        "%16, %17, %18, %19, %20, %21, %22, %23, %24, %25, %26, %27, %28, %29, %30, %31}, "
        "{%32, %33, %34, %35}, db, 1, 1, 1, 0;\n}\n"
        : "+f"(d[0]), "+f"(d[1]), "+f"(d[2]), "+f"(d[3]), "+f"(d[4]), "+f"(d[5]), "+f"(d[6]), "+f"(d[7]),
          "+f"(d[8]), "+f"(d[9]), "+f"(d[10]), "+f"(d[11]), "+f"(d[12]), "+f"(d[13]), "+f"(d[14]), "+f"(d[15]),
          "+f"(d[16]), "+f"(d[17]), "+f"(d[18]), "+f"(d[19]), "+f"(d[20]), "+f"(d[21]), "+f"(d[22]), "+f"(d[23]),
          "+f"(d[24]), "+f"(d[25]), "+f"(d[26]), "+f"(d[27]), "+f"(d[28]), "+f"(d[29]), "+f"(d[30]), "+f"(d[31])
        : "r"(a0), "r"(a1), "r"(a2), "r"(a3), "r"(blo), "r"(bhi));
}
__device__ __forceinline__ void mma_pv(float (&d)[12], uint32_t a0, uint32_t a1, uint32_t a2, uint32_t a3, uint32_t blo, uint32_t bhi) {
    asm volatile("{\n.reg .b64 da, db;\nmov.b64 db, {%16, %17};\n"
        "wgmma.mma_async.sync.aligned.m64n24k16.f32.bf16.bf16 "
        "{%0, %1, %2, %3, %4, %5, %6, %7, %8, %9, %10, %11}, "
        "{%12, %13, %14, %15}, db, 1, 1, 1, 1;\n}\n"
        : "+f"(d[0]), "+f"(d[1]), "+f"(d[2]), "+f"(d[3]), "+f"(d[4]), "+f"(d[5]), "+f"(d[6]), "+f"(d[7]),
          "+f"(d[8]), "+f"(d[9]), "+f"(d[10]), "+f"(d[11])
        : "r"(a0), "r"(a1), "r"(a2), "r"(a3), "r"(blo), "r"(bhi));
}
__device__ __forceinline__ void mma_ss_n72(float (&d)[36], uint32_t alo, uint32_t ahi, uint32_t blo, uint32_t bhi, uint32_t acc) {
    asm volatile("{\n.reg .b64 da, db;\n.reg .pred p;\nsetp.ne.u32 p, %40, 0;\nmov.b64 da, {%36, %37};\nmov.b64 db, {%38, %39};\n"
        "wgmma.mma_async.sync.aligned.m64n72k16.f32.bf16.bf16 "
        "{%0, %1, %2, %3, %4, %5, %6, %7, %8, %9, %10, %11, %12, %13, %14, %15, "
        "%16, %17, %18, %19, %20, %21, %22, %23, %24, %25, %26, %27, %28, %29, %30, %31, "
        "%32, %33, %34, %35}, "
        "da, db, p, 1, 1, 0, 1;\n}\n"
        : "+f"(d[0]), "+f"(d[1]), "+f"(d[2]), "+f"(d[3]), "+f"(d[4]), "+f"(d[5]), "+f"(d[6]), "+f"(d[7]),
          "+f"(d[8]), "+f"(d[9]), "+f"(d[10]), "+f"(d[11]), "+f"(d[12]), "+f"(d[13]), "+f"(d[14]), "+f"(d[15]),
          "+f"(d[16]), "+f"(d[17]), "+f"(d[18]), "+f"(d[19]), "+f"(d[20]), "+f"(d[21]), "+f"(d[22]), "+f"(d[23]),
          "+f"(d[24]), "+f"(d[25]), "+f"(d[26]), "+f"(d[27]), "+f"(d[28]), "+f"(d[29]), "+f"(d[30]), "+f"(d[31]),
          "+f"(d[32]), "+f"(d[33]), "+f"(d[34]), "+f"(d[35])
        : "r"(alo), "r"(ahi), "r"(blo), "r"(bhi), "r"(acc));
}
__device__ __forceinline__ void mma_ss_n192(float (&d)[96], uint32_t alo, uint32_t ahi, uint32_t blo, uint32_t bhi, uint32_t acc) {
    asm volatile("{\n.reg .b64 da, db;\n.reg .pred p;\nsetp.ne.u32 p, %100, 0;\nmov.b64 da, {%96, %97};\nmov.b64 db, {%98, %99};\n"
        "wgmma.mma_async.sync.aligned.m64n192k16.f32.bf16.bf16 "
        "{%0, %1, %2, %3, %4, %5, %6, %7, %8, %9, %10, %11, %12, %13, %14, %15, "
        "%16, %17, %18, %19, %20, %21, %22, %23, %24, %25, %26, %27, %28, %29, %30, %31, "
        "%32, %33, %34, %35, %36, %37, %38, %39, %40, %41, %42, %43, %44, %45, %46, %47, "
        "%48, %49, %50, %51, %52, %53, %54, %55, %56, %57, %58, %59, %60, %61, %62, %63, "
        "%64, %65, %66, %67, %68, %69, %70, %71, %72, %73, %74, %75, %76, %77, %78, %79, "
        "%80, %81, %82, %83, %84, %85, %86, %87, %88, %89, %90, %91, %92, %93, %94, %95}, "
        "da, db, p, 1, 1, 0, 1;\n}\n"
        : "+f"(d[0]), "+f"(d[1]), "+f"(d[2]), "+f"(d[3]), "+f"(d[4]), "+f"(d[5]), "+f"(d[6]), "+f"(d[7]),
          "+f"(d[8]), "+f"(d[9]), "+f"(d[10]), "+f"(d[11]), "+f"(d[12]), "+f"(d[13]), "+f"(d[14]), "+f"(d[15]),
          "+f"(d[16]), "+f"(d[17]), "+f"(d[18]), "+f"(d[19]), "+f"(d[20]), "+f"(d[21]), "+f"(d[22]), "+f"(d[23]),
          "+f"(d[24]), "+f"(d[25]), "+f"(d[26]), "+f"(d[27]), "+f"(d[28]), "+f"(d[29]), "+f"(d[30]), "+f"(d[31]),
          "+f"(d[32]), "+f"(d[33]), "+f"(d[34]), "+f"(d[35]), "+f"(d[36]), "+f"(d[37]), "+f"(d[38]), "+f"(d[39]),
          "+f"(d[40]), "+f"(d[41]), "+f"(d[42]), "+f"(d[43]), "+f"(d[44]), "+f"(d[45]), "+f"(d[46]), "+f"(d[47]),
          "+f"(d[48]), "+f"(d[49]), "+f"(d[50]), "+f"(d[51]), "+f"(d[52]), "+f"(d[53]), "+f"(d[54]), "+f"(d[55]),
          "+f"(d[56]), "+f"(d[57]), "+f"(d[58]), "+f"(d[59]), "+f"(d[60]), "+f"(d[61]), "+f"(d[62]), "+f"(d[63]),
          "+f"(d[64]), "+f"(d[65]), "+f"(d[66]), "+f"(d[67]), "+f"(d[68]), "+f"(d[69]), "+f"(d[70]), "+f"(d[71]),
          "+f"(d[72]), "+f"(d[73]), "+f"(d[74]), "+f"(d[75]), "+f"(d[76]), "+f"(d[77]), "+f"(d[78]), "+f"(d[79]),
          "+f"(d[80]), "+f"(d[81]), "+f"(d[82]), "+f"(d[83]), "+f"(d[84]), "+f"(d[85]), "+f"(d[86]), "+f"(d[87]),
          "+f"(d[88]), "+f"(d[89]), "+f"(d[90]), "+f"(d[91]), "+f"(d[92]), "+f"(d[93]), "+f"(d[94]), "+f"(d[95])
        : "r"(alo), "r"(ahi), "r"(blo), "r"(bhi), "r"(acc));
}
__device__ __forceinline__ void mma_rs_n64(float (&d)[32], uint32_t a0, uint32_t a1, uint32_t a2, uint32_t a3, uint32_t blo, uint32_t bhi, uint32_t acc) {
    asm volatile("{\n.reg .b64 da, db;\n.reg .pred p;\nsetp.ne.u32 p, %38, 0;\nmov.b64 db, {%36, %37};\n"
        "wgmma.mma_async.sync.aligned.m64n64k16.f32.bf16.bf16 "
        "{%0, %1, %2, %3, %4, %5, %6, %7, %8, %9, %10, %11, %12, %13, %14, %15, "
        "%16, %17, %18, %19, %20, %21, %22, %23, %24, %25, %26, %27, %28, %29, %30, %31}, "
        "{%32, %33, %34, %35}, db, p, 1, 1, 1;\n}\n"
        : "+f"(d[0]), "+f"(d[1]), "+f"(d[2]), "+f"(d[3]), "+f"(d[4]), "+f"(d[5]), "+f"(d[6]), "+f"(d[7]),
          "+f"(d[8]), "+f"(d[9]), "+f"(d[10]), "+f"(d[11]), "+f"(d[12]), "+f"(d[13]), "+f"(d[14]), "+f"(d[15]),
          "+f"(d[16]), "+f"(d[17]), "+f"(d[18]), "+f"(d[19]), "+f"(d[20]), "+f"(d[21]), "+f"(d[22]), "+f"(d[23]),
          "+f"(d[24]), "+f"(d[25]), "+f"(d[26]), "+f"(d[27]), "+f"(d[28]), "+f"(d[29]), "+f"(d[30]), "+f"(d[31])
        : "r"(a0), "r"(a1), "r"(a2), "r"(a3), "r"(blo), "r"(bhi), "r"(acc));
}

constexpr int A_THREADS = 384;
constexpr int A_STAGES = 5;
constexpr uint32_t A_STAGE_BYTES = 14336;
constexpr uint32_t A_OFF_W = 147456;
constexpr uint32_t A_OFF_MISC = A_OFF_W + 73728;
constexpr uint32_t A_SMEM = A_OFF_MISC + 4096 + 1024;

template <int ODD>
__device__ __forceinline__ void qkv_epilogue(const float (&acc)[112], uint32_t stg, uint32_t s_cs, float2 st0, float2 st1, int ct, int grp, int lane, float& vmax) {
    const int t = lane & 3, r = lane >> 2;
    const int nq = 32 - 12 * ct, nv = 64 - 12 * ct;
    const uint32_t selw0 = ((POLY_PATTERN >> (grp & 15)) & 1) ? 0x3F803F80u : 0u;
    const uint32_t selw1 = ((POLY_PATTERN >> ((grp + 1) & 15)) & 1) ? 0x3F803F80u : 0u;
#pragma unroll
    for (int j = 0; j < 27; j++) {
        const int s0 = (8 * j) / 18, d0 = (8 * j) % 18;
        int slot = s0, d = d0 + 2 * t;
        if (d0 + 6 >= 18 && d >= 18) { slot++; d -= 18; }
        const bool isv = slot >= nv, isq = slot < nq;
        const uint32_t gs = isv ? 384u : 128u;
        const uint32_t a0 = stg + slot * BLK_BYTES + (d >> 3) * (isv ? 128u : 2048u) + grp * gs + r * 16 + (d & 7) * 2;
        const float2 cs = lds64f(s_cs + (8 * (j + ODD) + 2 * t) * 4);
        const float sc = isq ? QSCALE : 1.f;
        const float f0 = st0.y * sc, f1 = st1.y * sc;
        const float* a = &acc[4 * (j + ODD)];
        const float v0 = (a[0] - st0.x * cs.x) * f0, v1 = (a[1] - st0.x * cs.y) * f0;
        const float v2 = (a[2] - st1.x * cs.x) * f1, v3 = (a[3] - st1.x * cs.y) * f1;
        vmax = fmaxf(vmax, fmaxf(fmaxf(fabsf(v0), fabsf(v1)), fmaxf(fabsf(v2), fabsf(v3))));
        const uint32_t w0 = pack_bf16(v0, v1), w1 = pack_bf16(v2, v3);
        if (d0 >= 10 && d0 <= 16 && d == 16) {
            const uint32_t p0 = isq ? 0x42FE47C0u : (isv ? 0x00003F80u : selw0);
            const uint32_t p1 = isq ? 0x42FE47C0u : (isv ? 0x00003F80u : selw1);
            sts128(a0, w0, p0, 0u, 0u);
            sts128(a0 + gs, w1, p1, 0u, 0u);
        } else {
            sts32(a0, w0);
            sts32(a0 + gs, w1);
        }
    }
}

__global__ void __launch_bounds__(A_THREADS, 1)
qkv_kernel(const __grid_constant__ CUtensorMap tm_x, const __grid_constant__ CUtensorMap tm_w,
           const __nv_bfloat16* __restrict__ x, const __nv_bfloat16* __restrict__ wqkv, const __nv_bfloat16* __restrict__ wo) {
    extern __shared__ uint8_t smem_raw[];
    const int tid = threadIdx.x, warp = tid >> 5, lane = tid & 31;
    pdl_launch();
    if (blockIdx.x >= 128) {
        const int hb = blockIdx.x - 128;
        for (int i = tid; i < 144 * 72; i += A_THREADS) {
            const int k = hb * 144 + i / 72, c = i % 72;
            const uint4 v = __ldg((const uint4*)(wo + (size_t)k * DM) + c);
            const int sl = c / 9, nc = c % 9;
            *(uint4*)(g_wo_img + sl * 82944 + (k >> 4) * 2304 + nc * 256 + ((k >> 3) & 1) * 128 + (k & 7) * 16) = v;
        }
        return;
    }
    const uint32_t sb = (smem_u32(smem_raw) + 1023u) & ~1023u;
    const uint32_t bar_a = sb + A_OFF_MISC, bar_full = bar_a + 72, bar_empty = bar_full + 40;
    const uint32_t s_cs = sb + A_OFF_MISC + 256, s_st = s_cs + 1024, s_red = s_st + 1024;
    const int rb = blockIdx.x & 15, ct = blockIdx.x >> 4;
    const uint32_t rank = blockIdx.x & 1;
    const int col0 = 216 * ct - 8 * (ct & 1);

    if (tid == 256) {
        for (int i = 0; i < 9; i++) mbar_init(bar_a + 8 * i, 1);
        for (int i = 0; i < A_STAGES; i++) { mbar_init(bar_full + 8 * i, 1); mbar_init(bar_empty + 8 * i, 4); }
        fence_mbar_init();
        mbar_expect(bar_a, 16384);
        tma_2d(sb, &tm_x, 0, rb * 128, bar_a);
    }
    __syncthreads();
    cluster_sync();

    if (warp == 8) {
        if (lane == 0) {
#pragma unroll 1
            for (int s = 0; s < 18; s++) {
                const int slot = s % A_STAGES;
                if (s >= A_STAGES) mbar_wait_cluster(bar_empty + 8 * slot, ((s / A_STAGES) - 1) & 1);
                mbar_expect(bar_full + 8 * slot, A_STAGE_BYTES);
                tma_3d_mc(sb + A_OFF_W + slot * A_STAGE_BYTES + rank * 7168, &tm_w, col0, s * 32 + rank * 16, bar_full + 8 * slot);
                if (s < 4) {
#pragma unroll 1
                    for (int kc = 1 + 2 * s; kc < 3 + 2 * s; kc++) {
                        mbar_expect(bar_a + 8 * kc, 16384);
                        tma_2d(sb + kc * 16384, &tm_x, kc * 64, rb * 128, bar_a + 8 * kc);
                    }
                }
            }
        }
    } else if (warp > 8) {
        const int t = tid - 288;
        if (blockIdx.x == 0) for (int i = t; i < 16 + 16 * 9 * 8; i += 96) g_flag_c[i] = 0;
        const int ntask = rb < 11 ? 8 : 6;
        uint4 v[3][9];
#pragma unroll
        for (int n = 0; n < 3; n++) {
            const int q = warp - 9 + 3 * n;
            if (q < ntask) {
                const __nv_bfloat16* p = q < 4 ? x + (size_t)(rb * 128 + ct * 16 + q * 4 + (lane >> 3)) * DM + (lane & 7) * 8
                                               : wqkv + (size_t)((q & 1) * 288 + lane) * 1728 + ct * 216 + (rb + 16 * ((q - 4) >> 1)) * 8;
                const int stride = q < 4 ? 64 : 32 * 1728;
#pragma unroll
                for (int i = 0; i < 9; i++) v[n][i] = __ldg((const uint4*)(p + (size_t)i * stride));
            }
        }
#pragma unroll
        for (int n = 0; n < 3; n++) {
            const int q = warp - 9 + 3 * n;
            if (q < ntask) {
                float c[8] = {0.f, 0.f, 0.f, 0.f, 0.f, 0.f, 0.f, 0.f};
#pragma unroll
                for (int i = 0; i < 9; i++) {
                    c[0] += bf_lo(v[n][i].x); c[1] += bf_hi(v[n][i].x); c[2] += bf_lo(v[n][i].y); c[3] += bf_hi(v[n][i].y);
                    c[4] += bf_lo(v[n][i].z); c[5] += bf_hi(v[n][i].z); c[6] += bf_lo(v[n][i].w); c[7] += bf_hi(v[n][i].w);
                }
                if (q < 4) {
                    float sum = ((c[0] + c[1]) + (c[2] + c[3])) + ((c[4] + c[5]) + (c[6] + c[7]));
                    sum += __shfl_xor_sync(~0u, sum, 1); sum += __shfl_xor_sync(~0u, sum, 2); sum += __shfl_xor_sync(~0u, sum, 4);
                    const float mean = sum * (1.f / DM);
                    float sq = 0.f;
#pragma unroll
                    for (int i = 0; i < 9; i++) {
                        const uint32_t w[4] = {v[n][i].x, v[n][i].y, v[n][i].z, v[n][i].w};
#pragma unroll
                        for (int k = 0; k < 4; k++) { const float a = bf_lo(w[k]) - mean, b = bf_hi(w[k]) - mean; sq += a * a + b * b; }
                    }
                    sq += __shfl_xor_sync(~0u, sq, 1); sq += __shfl_xor_sync(~0u, sq, 2); sq += __shfl_xor_sync(~0u, sq, 4);
                    if ((lane & 7) == 0) g_xstat[rb * 128 + ct * 16 + q * 4 + (lane >> 3)] = make_float2(mean, 1.f / sqrtf(sq * (1.f / DM) + LN_EPS));
                } else {
#pragma unroll
                    for (int k = 0; k < 8; k++) {
#pragma unroll
                        for (int o = 16; o > 0; o >>= 1) c[k] += __shfl_xor_sync(~0u, c[k], o);
                    }
                    if (lane == 0) {
#pragma unroll
                        for (int k = 0; k < 8; k++) sts32(s_red + ((q - 4) * 8 + k) * 4, __float_as_uint(c[k]));
                    }
                }
            }
        }
        nbar_sync(1, 96);
        if (t < 16 && rb + 16 * (t >> 3) < 27) {
            const uint32_t a = s_red + ((t >> 3) * 16 + (t & 7)) * 4;
            g_cs0[ct * 216 + (rb + 16 * (t >> 3)) * 8 + (t & 7)] = __uint_as_float(lds32(a)) + __uint_as_float(lds32(a + 32));
        }
        __syncwarp();
        if (t == 0) {
            fence_gpu();
            flag_add(&g_cnt_a[rb]);
            flag_add(&g_cnt_a[16 + ct]);
            flag_wait(&g_cnt_a[rb], 8);
            flag_wait(&g_cnt_a[16 + ct], 16);
        }
        nbar_sync(1, 96);
        for (int i = t; i < 128; i += 96) {
            const float2 st = __ldcg(&g_xstat[rb * 128 + i]);
            asm volatile("st.shared.v2.f32 [%0], {%1, %2};" :: "r"(s_st + i * 8), "f"(st.x), "f"(st.y) : "memory");
        }
        for (int i = t; i < 224; i += 96) {
            const int c = i - 8 * (ct & 1);
            sts32(s_cs + i * 4, (c >= 0 && c < 216) ? __float_as_uint(__ldcg(&g_cs0[ct * 216 + c])) : 0u);
        }
        nbar_arrive(2, 352);
    } else {
        const int wg = warp >> 2;
        float acc[112];
#pragma unroll
        for (int i = 0; i < 112; i++) acc[i] = 0.f;
        const uint32_t a_lo = desc_addr(sb + wg * 8192) | (1u << 16);
        const uint32_t b_lo = desc_addr(sb + A_OFF_W) | ((1024 >> 4) << 16);
        const uint32_t rel = (tid & 127) == 0 ? bar_empty : mapa(bar_empty, rank ^ 1);
        const bool do_rel = (tid & 95) == 0;
        int slot = 0, prev = 0;
        uint32_t ph = 0;
#pragma unroll 1
        for (int s = 0; s < 18; s++) {
            if (!(s & 1)) mbar_wait(bar_a + 4 * s, 0);
            mbar_wait(bar_full + 8 * slot, ph);
            const uint32_t al = a_lo + (s >> 1) * 1024 + (s & 1) * 4, bl = b_lo + slot * (A_STAGE_BYTES >> 4);
            wg_fence();
            mma_ss_n224(acc, al, HI_SW128, bl, HI_SW64, 1);
            mma_ss_n224(acc, al + 2, HI_SW128, bl + (7168 >> 4), HI_SW64, 1);
            wg_commit();
            wg_wait<1>();
            if (do_rel && s >= 1 && s <= 18 - A_STAGES) mbar_arrive_cluster(rel + 8 * prev);
            prev = slot;
            if (++slot == A_STAGES) { slot = 0; ph ^= 1; }
        }
        wg_wait<0>();
        fence_regs(acc);
        nbar_sync(2, 352);
        const int grp = warp * 2;
        const float2 st0 = lds64f(s_st + (warp * 16 + (lane >> 2)) * 8), st1 = lds64f(s_st + (warp * 16 + 8 + (lane >> 2)) * 8);
        float vmax = 0.f;
        if (ct & 1) qkv_epilogue<1>(acc, sb, s_cs, st0, st1, ct, grp, lane, vmax);
        else qkv_epilogue<0>(acc, sb, s_cs, st0, st1, ct, grp, lane, vmax);
        fence_async_smem();
        nbar_sync(3, 256);
        if (tid < 12) {
            bulk_store(g_qkv + (size_t)(ct * 12 + tid) * SLOT_BYTES + rb * BLK_BYTES, sb + tid * BLK_BYTES, BLK_BYTES);
            bulk_commit();
        }
#pragma unroll
        for (int o = 16; o > 0; o >>= 1) vmax = fmaxf(vmax, __shfl_xor_sync(~0u, vmax, o));
        if (lane == 0) g_kmax[ct * 128 + rb * 8 + warp] = vmax;
        if (tid < 12) bulk_wait_read();
    }
}

constexpr uint32_t B_SMEM = 2 * SLOT_BYTES + 64;
constexpr uint32_t QK_LBO = (2048 >> 4) << 16, V_LBO = (384 >> 4) << 16, HI_NOSW = 128 >> 4;

__device__ __forceinline__ uint32_t exp_pair_poly(float a, float b) {
    const uint32_t u = __byte_perm(__float_as_uint(a), __float_as_uint(b), 0x5410);
    uint32_t g, w, p, r;
    asm("lop3.b32 %0, %1, 0x007F007F, 0x48004800, 0xEA;" : "=r"(g) : "r"(u));
    asm("fma.rn.f16x2 %0, %1, %2, %3;" : "=r"(w) : "r"(g), "r"(0x38A038A0u), "r"(0xC40EC40Eu));
    asm("fma.rn.f16x2 %0, %1, %1, %2;" : "=r"(p) : "r"(w), "r"(0x47AE47AEu));
    asm("lop3.b32 %0, %1, %2, 0x007F007F, 0xD8;" : "=r"(r) : "r"(u), "r"(p));
    return r;
}
template <int JOFF>
__device__ __forceinline__ void exp_tile(const float (&s)[32], uint32_t (&p)[16]) {
#pragma unroll
    for (int j = 0; j < 8; j++) {
        if ((POLY_PATTERN >> (j + JOFF)) & 1) {
            p[2 * j] = exp_pair_poly(s[4 * j], s[4 * j + 1]);
            p[2 * j + 1] = exp_pair_poly(s[4 * j + 2], s[4 * j + 3]);
        } else {
            p[2 * j] = pack_bf16(ex2(s[4 * j]), ex2(s[4 * j + 1]));
            p[2 * j + 1] = pack_bf16(ex2(s[4 * j + 2]), ex2(s[4 * j + 3]));
        }
    }
}
__device__ __forceinline__ void qk_tile(float (&s)[32], const uint32_t (&q)[8], uint32_t k) {
    mma_qk_first(s, q[0], q[1], q[2], q[3], k + QK_LBO, HI_NOSW);
    mma_qk_second(s, q[4], q[5], q[6], q[7], k + 256, HI_NOSW);
}
__device__ __forceinline__ void pv_tile(float (&o)[12], const uint32_t (&p)[16], uint32_t v) {
#pragma unroll
    for (int kk = 0; kk < 4; kk++) mma_pv(o, p[4 * kk], p[4 * kk + 1], p[4 * kk + 2], p[4 * kk + 3], v + kk * 48, HI_NOSW);
}
__device__ __forceinline__ bool wg_any(bool pred, uint32_t id) {
    uint32_t r;
    asm volatile("{\n.reg .pred p, q;\nsetp.ne.u32 p, %1, 0;\nbar.red.or.pred q, %2, 128, p;\nselp.u32 %0, 1, 0, q;\n}\n" : "=r"(r) : "r"((uint32_t)pred), "r"(id) : "memory");
    return r;
}
__device__ __forceinline__ void attn_safe_block(uint32_t k0, uint32_t (&q)[8], float (&o)[12]) {
    if (threadIdx.x & 3) { q[4] = 0; q[5] = 0; }
    float s[32], m0 = -INFINITY, m1 = -INFINITY;
    uint32_t p[16];
#pragma unroll
    for (int i = 0; i < 12; i++) o[i] = 0.f;
#pragma unroll 1
    for (int i = 0; i < 32; i++) {
        wg_fence();
        qk_tile(s, q, k0 + (i >> 1) * 384 + (i & 1) * 64);
        wg_commit();
        wg_wait<0>();
        fence_regs(s);
        float n0 = m0, n1 = m1;
#pragma unroll
        for (int j = 0; j < 8; j++) { n0 = fmaxf(n0, fmaxf(s[4 * j], s[4 * j + 1])); n1 = fmaxf(n1, fmaxf(s[4 * j + 2], s[4 * j + 3])); }
        n0 = fmaxf(n0, __shfl_xor_sync(~0u, n0, 1)); n0 = fmaxf(n0, __shfl_xor_sync(~0u, n0, 2));
        n1 = fmaxf(n1, __shfl_xor_sync(~0u, n1, 1)); n1 = fmaxf(n1, __shfl_xor_sync(~0u, n1, 2));
        const float c0 = ex2(m0 - n0), c1 = ex2(m1 - n1);
        m0 = n0; m1 = n1;
#pragma unroll
        for (int j = 0; j < 3; j++) { o[4 * j] *= c0; o[4 * j + 1] *= c0; o[4 * j + 2] *= c1; o[4 * j + 3] *= c1; }
#pragma unroll
        for (int j = 0; j < 8; j++) {
            p[2 * j] = pack_bf16(ex2(s[4 * j] - m0), ex2(s[4 * j + 1] - m0));
            p[2 * j + 1] = pack_bf16(ex2(s[4 * j + 2] - m1), ex2(s[4 * j + 3] - m1));
        }
        fence_regs(o);
        wg_fence();
        pv_tile(o, p, k0 + (SLOT_BYTES >> 4) + V_LBO + i * 192);
        wg_commit();
        wg_wait<0>();
        fence_regs(o);
    }
}

__global__ void __launch_bounds__(512, 1)
attn_kernel(const __nv_bfloat16* __restrict__ w1, const __nv_bfloat16* __restrict__ w2) {
    extern __shared__ __align__(128) uint8_t smem_raw[];
    const int tid = threadIdx.x, lane = tid & 31;
    if (blockIdx.x < 4) {
        pdl_launch();
        if (tid < 64) l2_prefetch((const uint8_t*)w2 + (size_t)(blockIdx.x * 64 + tid) * 20736, 20736);
        float* red = (float*)smem_raw;
        const int cg = tid % 144, part = tid / 144;
        float c[8] = {0.f, 0.f, 0.f, 0.f, 0.f, 0.f, 0.f, 0.f};
        if (part < 3) {
            const uint4* pw = (const uint4*)(w1 + (size_t)part * 192 * FF + blockIdx.x * 1152) + cg;
#pragma unroll 8
            for (int k = 0; k < 192; k++) {
                const uint4 v = __ldg(pw + (size_t)k * (FF / 8));
                c[0] += bf_lo(v.x); c[1] += bf_hi(v.x); c[2] += bf_lo(v.y); c[3] += bf_hi(v.y);
                c[4] += bf_lo(v.z); c[5] += bf_hi(v.z); c[6] += bf_lo(v.w); c[7] += bf_hi(v.w);
            }
#pragma unroll
            for (int k = 0; k < 8; k++) red[part * 1152 + cg * 8 + k] = c[k];
        }
        __syncthreads();
        for (int i = tid; i < 1152; i += 512) g_cs1[blockIdx.x * 1152 + i] = red[i] + red[1152 + i] + red[2304 + i];
        return;
    }
    const uint32_t sk = smem_u32(smem_raw), sv = sk + SLOT_BYTES, bar = sv + SLOT_BYTES;
    const int h = (blockIdx.x - 4) >> 2, qt = blockIdx.x & 3;
    if (tid == 0) {
        for (int i = 0; i < 4; i++) mbar_init(bar + 8 * i, 1);
        fence_mbar_init();
    }
    __syncthreads();
    pdl_wait();
    pdl_launch();
    {
        const uint8_t* gk = g_qkv + (size_t)(32 + h) * SLOT_BYTES;
        const uint8_t* gv = g_qkv + (size_t)(64 + h) * SLOT_BYTES;
        if (tid == 0) {
            mbar_expect(bar, 4 * BLK_BYTES);
            bulk_load(sk, gk, 2 * BLK_BYTES, bar);
            bulk_load(sv, gv, 2 * BLK_BYTES, bar);
        }
        if (tid == 384) {
            mbar_wait(bar, 0);
#pragma unroll
            for (int c = 1; c < 4; c++) {
                const uint32_t off = (uint32_t)BLK_BYTES << c;
                mbar_expect(bar + 8 * c, 2 * off);
                bulk_load(sk + off, gk + off, off, bar + 8 * c);
                bulk_load(sv + off, gv + off, off, bar + 8 * c);
            }
        }
    }
    float kmax;
    {
        const float4 v = __ldcg((const float4*)(g_kmax + ((576 + 18 * h) / 216) * 128) + lane);
        kmax = fmaxf(fmaxf(v.x, v.y), fmaxf(v.z, v.w));
#pragma unroll
        for (int o = 16; o > 0; o >>= 1) kmax = fmaxf(kmax, __shfl_xor_sync(~0u, kmax, o));
    }
    const uint32_t k0 = desc_addr(sk);
#pragma unroll 1
    for (int u = 0; u < 2; u++) {
        const int row0 = qt * 512 + u * 256 + (tid >> 5) * 16;
        uint32_t q[8];
        {
            const uint8_t* gq = g_qkv + (size_t)h * SLOT_BYTES + (row0 >> 7) * BLK_BYTES + ((row0 >> 3) & 15) * 128 + lane * 4;
            q[0] = __ldcg((const uint32_t*)(gq)); q[1] = __ldcg((const uint32_t*)(gq + 128));
            q[2] = __ldcg((const uint32_t*)(gq + 2048)); q[3] = __ldcg((const uint32_t*)(gq + 2048 + 128));
            q[4] = __ldcg((const uint32_t*)(gq + 4096)); q[5] = __ldcg((const uint32_t*)(gq + 4096 + 128));
            q[6] = 0; q[7] = 0;
        }
        bool unsafe;
        {
            const bool first = (lane & 3) == 0;
            float n0 = fabsf(bf_lo(q[0])) + fabsf(bf_hi(q[0])) + fabsf(bf_lo(q[2])) + fabsf(bf_hi(q[2])) + (first ? fabsf(bf_lo(q[4])) + fabsf(bf_hi(q[4])) : 0.f);
            float n1 = fabsf(bf_lo(q[1])) + fabsf(bf_hi(q[1])) + fabsf(bf_lo(q[3])) + fabsf(bf_hi(q[3])) + (first ? fabsf(bf_lo(q[5])) + fabsf(bf_hi(q[5])) : 0.f);
            n0 += __shfl_xor_sync(~0u, n0, 1); n0 += __shfl_xor_sync(~0u, n0, 2);
            n1 += __shfl_xor_sync(~0u, n1, 1); n1 += __shfl_xor_sync(~0u, n1, 2);
            unsafe = wg_any(!(fmaxf(n0, n1) * kmax <= 100.f), 1 + (tid >> 7));
        }
        float o[12];
#pragma unroll
        for (int i = 0; i < 12; i++) o[i] = 0.f;
        if (!unsafe) {
            fence_regs(o); fence_regs(q);
            float s[32]; uint32_t p[16];
            uint32_t k = k0;
#pragma unroll 1
            for (int seg = 0; seg < 4; seg++) {
                mbar_wait(bar + 8 * seg, 0);
                const uint32_t kend = k0 + (768u << seg);
#pragma unroll 1
                for (; k < kend; k += 384) {
                    wg_fence();
                    qk_tile(s, q, k);
                    wg_commit();
                    wg_wait<0>();
                    fence_regs(s); fence_regs(p);
                    exp_tile<0>(s, p);
                    wg_fence();
                    pv_tile(o, p, k + (SLOT_BYTES >> 4) + V_LBO);
                    qk_tile(s, q, k + 64);
                    wg_commit();
                    wg_wait<0>();
                    fence_regs(s); fence_regs(p);
                    exp_tile<8>(s, p);
                    wg_fence();
                    pv_tile(o, p, k + (SLOT_BYTES >> 4) + V_LBO + 192);
                    wg_commit();
                }
            }
            wg_wait<0>();
            fence_regs(o);
            float chk = 0.f;
#pragma unroll
            for (int i = 0; i < 12; i++) chk += fabsf(o[i]);
            unsafe = wg_any(!(chk < INFINITY), 1 + (tid >> 7));
        }
        if (unsafe) {
#pragma unroll 1
            for (int seg = 0; seg < 4; seg++) mbar_wait(bar + 8 * seg, 0);
            attn_safe_block(k0, q, o);
        }
        const float r0 = 1.f / __shfl_sync(~0u, o[8], (lane & ~3) | 1), r1 = 1.f / __shfl_sync(~0u, o[10], (lane & ~3) | 1);
        __nv_bfloat16* po = g_attn + (size_t)(row0 + (lane >> 2)) * DM + h * 18 + (lane & 3) * 2;
#pragma unroll
        for (int j = 0; j < 3; j++) {
            if (j < 2 || (lane & 3) == 0) {
                *(uint32_t*)(po + 8 * j) = pack_bf16(o[4 * j] * r0, o[4 * j + 1] * r0);
                *(uint32_t*)(po + 8 * DM + 8 * j) = pack_bf16(o[4 * j + 2] * r1, o[4 * j + 3] * r1);
            }
        }
    }
}

constexpr uint32_t C_OFF_W = 147456, C_STAGE = 12288;
constexpr uint32_t C_OFF_CS = C_OFF_W + 6 * C_STAGE;
constexpr uint32_t C_OFF_BAR = C_OFF_W + 82944;
constexpr uint32_t C_SMEM = C_OFF_BAR + 512 + 1024;

struct RowStat { float mean, rstd; };
__device__ __forceinline__ RowStat combine_hstat(int row, int t) {
    const float4 v = __ldcg((const float4*)(g_hstat + (size_t)row * 8) + t);
    float sum = v.x + v.z;
    sum += __shfl_xor_sync(~0u, sum, 1); sum += __shfl_xor_sync(~0u, sum, 2);
    const float mean = sum * (1.f / DM);
    const float d0 = v.x * (1.f / 72) - mean, d1 = v.z * (1.f / 72) - mean;
    float m2 = v.y + v.w + 72.f * (d0 * d0 + d1 * d1);
    m2 += __shfl_xor_sync(~0u, m2, 1); m2 += __shfl_xor_sync(~0u, m2, 2);
    return {mean, 1.f / sqrtf(m2 * (1.f / DM) + LN_EPS)};
}

__global__ void __launch_bounds__(384, 1)
ffn_kernel(const __grid_constant__ CUtensorMap tm_attn, const __grid_constant__ CUtensorMap tm_h,
           const __grid_constant__ CUtensorMap tm_w1, const __grid_constant__ CUtensorMap tm_w2,
           const __grid_constant__ CUtensorMap tm_out, const __nv_bfloat16* __restrict__ x) {
    extern __shared__ uint8_t smem_raw[];
    const int tid = threadIdx.x, warp = tid >> 5, lane = tid & 31;
    const uint32_t sb = (smem_u32(smem_raw) + 1023u) & ~1023u;
    const uint32_t bar_a = sb + C_OFF_BAR, bar_full = bar_a + 72, bar_empty = bar_full + 48;
    const uint32_t bar_wo = bar_empty + 48, bar_cs = bar_wo + 8, bar_g1 = bar_cs + 8, bar_recv = bar_g1 + 8, bar_rfree = bar_recv + 8;
    const uint32_t bar_pub = bar_rfree + 8;
    const int rb = blockIdx.x & 15, e = blockIdx.x >> 4;
    const uint32_t rank = blockIdx.x & 1;
    const int wrb = blockIdx.x >> 3, wsl = blockIdx.x & 7;
    const int start = e < 7 ? e + 1 : 0;

    if (tid == 256) {
        for (int i = 0; i < 9; i++) mbar_init(bar_a + 8 * i, 1);
        for (int i = 0; i < 6; i++) { mbar_init(bar_full + 8 * i, 1); mbar_init(bar_empty + 8 * i, 4); }
        mbar_init(bar_wo, 1); mbar_init(bar_cs, 1); mbar_init(bar_g1, 2); mbar_init(bar_recv, 1); mbar_init(bar_rfree, 2);
        for (int i = 0; i < 18; i++) mbar_init(bar_pub + 8 * i, 4);
        fence_mbar_init();
        mbar_expect(bar_wo, 82944);
#pragma unroll 1
        for (int i = 0; i < 3; i++) bulk_load(sb + C_OFF_W + i * 27648, g_wo_img + wsl * 82944 + i * 27648, 27648, bar_wo);
        tma_prefetch_desc(&tm_attn); tma_prefetch_desc(&tm_h); tma_prefetch_desc(&tm_w1); tma_prefetch_desc(&tm_w2);
    }
    __syncthreads();
    cluster_sync();

    if (warp >= 8) {
        asm volatile("setmaxnreg.dec.sync.aligned.u32 40;");
        if (warp == 8) {
            if (lane == 0) {
                pdl_wait();
                if (blockIdx.x == 0) for (int i = 0; i < 24; i++) g_cnt_a[i] = 0;
#pragma unroll 1
                for (int kc = 0; kc < 9; kc++) {
                    mbar_expect(bar_a + 8 * kc, 16384);
                    tma_2d_mc(sb + kc * 16384 + rank * 8192, &tm_attn, kc * 64, wrb * 128 + rank * 64, bar_a + 8 * kc);
                }
                int slot = 0;
                uint32_t ph = 0;
#pragma unroll 1
                for (int s = 0; s < 108; s++) {
                    mbar_wait_cluster(bar_empty + 8 * slot, ph);
                    mbar_expect(bar_full + 8 * slot, C_STAGE);
                    const uint32_t dst = sb + C_OFF_W + slot * C_STAGE + rank * 6144;
                    if (s < 54) {
                        const int pass = s / 18, ks = s - pass * 18;
                        tma_3d_mc(dst, &tm_w1, e * 576 + pass * 192, ks * 32 + rank * 16, bar_full + 8 * slot);
                    } else {
                        int sl = start + (s - 54) / 6;
                        if (sl >= 9) sl -= 9;
                        tma_2d_mc(dst, &tm_w2, sl * 64, e * 576 + slot * 96 + rank * 48, bar_full + 8 * slot);
                    }
                    if (s == 5) {
                        mbar_expect(bar_cs, 2304);
                        bulk_load(sb + C_OFF_CS, g_cs1 + e * 576, 2304, bar_cs);
                        flag_wait(&g_flag_c[rb], 16);
                        fence_async_all();
#pragma unroll 1
                        for (int kc = 0; kc < 9; kc++) {
                            mbar_expect(bar_a + 8 * kc, 16384);
                            tma_2d(sb + kc * 16384, &tm_h, kc * 64, rb * 128, bar_a + 8 * kc);
                        }
                    }
                    if (++slot == 6) { slot = 0; ph ^= 1; }
                }
            }
        } else if (warp == 11) {
            if (lane == 0) {
                mbar_wait(bar_g1, 0);
#pragma unroll 1
                for (int sl = e; sl < (e == 7 ? 9 : e + 1); sl++) {
                    if (sl == 8) mbar_wait(bar_rfree, 0);
                    mbar_expect(bar_recv, 7 * 16384);
                    int j = 0;
#pragma unroll 1
                    for (int p = 0; p < 8; p++) {
                        int st = sl - p;
                        if (st < 0) st += 9;
                        const int c = st == 0 ? 7 : st - 1;
                        if (st == 8 || c == e) continue;
                        flag_wait(&g_flag_c[16 + (rb * 9 + sl) * 8 + c], 2);
                        fence_async_all();
                        bulk_load(sb + (j < e ? j : j + 1) * 16384, g_part + (size_t)((rb * 9 + sl) * 8 + c) * 16384, 16384, bar_recv);
                        j++;
                    }
                }
            }
        } else {
            if (lane == 0) {
                const uint32_t pb = bar_pub + (warp - 9) * 72;
                mbar_wait(pb, 0);
                fence_gpu();
                flag_add(&g_flag_c[wrb]);
                const int nout = e == 7 ? 7 : 8;
#pragma unroll 1
                for (int p = 0; p < nout; p++) {
                    int sl = start + p;
                    if (sl >= 9) sl -= 9;
                    mbar_wait(pb + 8 + 8 * p, 0);
                    fence_gpu();
                    flag_add(&g_flag_c[16 + (rb * 9 + sl) * 8 + e]);
                }
            }
        }
    } else {
        asm volatile("setmaxnreg.inc.sync.aligned.u32 232;");
        const int wg = warp >> 2, t = lane & 3, r = lane >> 2;
        const uint32_t a_lo = desc_addr(sb + wg * 8192) | (1u << 16);
        const uint32_t rel = (tid & 127) == 0 ? bar_empty : mapa(bar_empty, rank ^ 1);
        const bool do_rel = (tid & 95) == 0;
        {
            const int row = wrb * 128 + warp * 16 + r;
            const uint32_t* px = (const uint32_t*)(x + (size_t)row * DM + wsl * 72) + t;
            uint32_t xr[18];
#pragma unroll
            for (int j = 0; j < 9; j++) { xr[2 * j] = __ldg(px + 4 * j); xr[2 * j + 1] = __ldg(px + 8 * (DM / 2) + 4 * j); }
            float acc[36];
#pragma unroll
            for (int i = 0; i < 36; i++) acc[i] = 0.f;
            fence_regs(acc);
            const uint32_t b_lo = desc_addr(sb + C_OFF_W) | ((128 >> 4) << 16);
            mbar_wait(bar_wo, 0);
#pragma unroll 1
            for (int kc = 0; kc < 9; kc++) {
                mbar_wait(bar_a + 8 * kc, 0);
                wg_fence();
#pragma unroll
                for (int j = 0; j < 4; j++) mma_ss_n72(acc, a_lo + kc * 1024 + j * 2, HI_SW128, b_lo + (kc * 4 + j) * 144, 256 >> 4, 1);
                wg_commit();
            }
            wg_wait<0>();
            fence_regs(acc);
            if (do_rel) {
#pragma unroll
                for (int i = 0; i < 6; i++) mbar_arrive_cluster(rel + 8 * i);
            }
            uint32_t* ph = (uint32_t*)(g_h + (size_t)row * DM + wsl * 72) + t;
            float s0 = 0.f, s1 = 0.f;
#pragma unroll
            for (int j = 0; j < 9; j++) {
                const uint32_t w0 = pack_bf16(acc[4 * j] + bf_lo(xr[2 * j]), acc[4 * j + 1] + bf_hi(xr[2 * j]));
                const uint32_t w1 = pack_bf16(acc[4 * j + 2] + bf_lo(xr[2 * j + 1]), acc[4 * j + 3] + bf_hi(xr[2 * j + 1]));
                ph[4 * j] = w0; ph[8 * (DM / 2) + 4 * j] = w1;
                acc[4 * j] = bf_lo(w0); acc[4 * j + 1] = bf_hi(w0); acc[4 * j + 2] = bf_lo(w1); acc[4 * j + 3] = bf_hi(w1);
                s0 += acc[4 * j] + acc[4 * j + 1]; s1 += acc[4 * j + 2] + acc[4 * j + 3];
            }
            s0 += __shfl_xor_sync(~0u, s0, 1); s0 += __shfl_xor_sync(~0u, s0, 2);
            s1 += __shfl_xor_sync(~0u, s1, 1); s1 += __shfl_xor_sync(~0u, s1, 2);
            const float m0 = s0 * (1.f / 72), m1 = s1 * (1.f / 72);
            float q0 = 0.f, q1 = 0.f;
#pragma unroll
            for (int j = 0; j < 9; j++) {
                const float a = acc[4 * j] - m0, b = acc[4 * j + 1] - m0, c = acc[4 * j + 2] - m1, d = acc[4 * j + 3] - m1;
                q0 += a * a + b * b; q1 += c * c + d * d;
            }
            q0 += __shfl_xor_sync(~0u, q0, 1); q0 += __shfl_xor_sync(~0u, q0, 2);
            q1 += __shfl_xor_sync(~0u, q1, 1); q1 += __shfl_xor_sync(~0u, q1, 2);
            if (t == 0) { g_hstat[(size_t)row * 8 + wsl] = make_float2(s0, q0); g_hstat[(size_t)(row + 8) * 8 + wsl] = make_float2(s1, q1); }
            __syncwarp();
            if (lane == 0) mbar_arrive(bar_pub + wg * 72);
        }
        uint32_t hreg[144];
        RowStat st0, st1;
        uint32_t ph = 0;
#pragma unroll
        for (int pass = 0; pass < 3; pass++) {
            float acc[96];
            const uint32_t b_lo = desc_addr(sb + C_OFF_W) | ((2048 >> 4) << 16);
#pragma unroll 1
            for (int i = 0; i < 3; i++) {
#pragma unroll
                for (int st = 0; st < 6; st++) {
                    if (pass == 0 && !(st & 1)) mbar_wait(bar_a + 8 * (3 * i + st / 2), 1);
                    mbar_wait(bar_full + 8 * st, ph);
                    const uint32_t al = a_lo + (3 * i + st / 2) * 1024 + (st & 1) * 4, bl = b_lo + st * (C_STAGE >> 4);
                    wg_fence();
                    mma_ss_n192(acc, al, HI_SW128, bl, HI_SW128, st > 0 ? 1u : (uint32_t)i);
                    mma_ss_n192(acc, al + 2, HI_SW128, bl + (6144 >> 4), HI_SW128, 1);
                    wg_commit();
                    wg_wait<1>();
                    if (do_rel && (st > 0 || i > 0)) mbar_arrive_cluster(rel + 8 * ((st + 5) % 6));
                }
                ph ^= 1;
            }
            if (pass == 0) {
                st0 = combine_hstat(rb * 128 + warp * 16 + r, t);
                st1 = combine_hstat(rb * 128 + warp * 16 + r + 8, t);
                mbar_wait(bar_cs, 0);
            }
            wg_wait<0>();
            fence_regs(acc);
            if (do_rel) mbar_arrive_cluster(rel + 8 * 5);
            if (pass == 2 && (tid & 127) == 0) mbar_arrive(bar_g1);
#pragma unroll
            for (int j = 0; j < 24; j++) {
                const float2 cs = lds64f(sb + C_OFF_CS + (pass * 192 + 8 * j + 2 * t) * 4);
                hreg[pass * 48 + 2 * j] = pack_bf16_relu(acc[4 * j] - st0.mean * cs.x, acc[4 * j + 1] - st0.mean * cs.y);
                hreg[pass * 48 + 2 * j + 1] = pack_bf16_relu(acc[4 * j + 2] - st1.mean * cs.x, acc[4 * j + 3] - st1.mean * cs.y);
            }
        }
        fence_regs(hreg);
        const uint32_t b_lo = desc_addr(sb + C_OFF_W) | (1u << 16);
        int sl = start;
        uint32_t rph = 0;
#pragma unroll 1
        for (int p = 0; p < 9; p++) {
            float acc[32];
#pragma unroll
            for (int st = 0; st < 6; st++) {
                mbar_wait(bar_full + 8 * st, ph);
                wg_fence();
#pragma unroll
                for (int j = 0; j < 6; j++) {
                    const int kk = st * 6 + j;
                    mma_rs_n64(acc, hreg[4 * kk], hreg[4 * kk + 1], hreg[4 * kk + 2], hreg[4 * kk + 3], b_lo + st * (C_STAGE >> 4) + j * 128, HI_SW128, kk > 0 ? 1u : 0u);
                }
                wg_commit();
                wg_wait<1>();
                if (do_rel && st > 0 && p < 8) mbar_arrive_cluster(rel + 8 * (st - 1));
            }
            wg_wait<0>();
            fence_regs(acc);
            if (do_rel && p < 8) mbar_arrive_cluster(rel + 8 * 5);
            ph ^= 1;
            if (sl != e && !(e == 7 && sl == 8)) {
                uint4* dst = (uint4*)(g_part + (size_t)((rb * 9 + sl) * 8 + e) * 16384 + wg * 8192) + (tid & 127);
#pragma unroll
                for (int i = 0; i < 4; i++)
                    dst[i * 128] = make_uint4(pack_bf16(acc[8 * i], acc[8 * i + 1]), pack_bf16(acc[8 * i + 2], acc[8 * i + 3]),
                                              pack_bf16(acc[8 * i + 4], acc[8 * i + 5]), pack_bf16(acc[8 * i + 6], acc[8 * i + 7]));
                __syncwarp();
                if (lane == 0) mbar_arrive(bar_pub + wg * 72 + 8 + 8 * p);
            } else {
                mbar_wait(bar_recv, rph);
                rph ^= 1;
#pragma unroll 1
                for (int j = 0; j < 7; j++) {
                    const uint32_t src = sb + (j < e ? j : j + 1) * 16384 + wg * 8192 + (tid & 127) * 16;
#pragma unroll
                    for (int i = 0; i < 4; i++) {
                        const uint4 v = lds128(src + i * 2048);
                        acc[8 * i] += bf_lo(v.x); acc[8 * i + 1] += bf_hi(v.x); acc[8 * i + 2] += bf_lo(v.y); acc[8 * i + 3] += bf_hi(v.y);
                        acc[8 * i + 4] += bf_lo(v.z); acc[8 * i + 5] += bf_hi(v.z); acc[8 * i + 6] += bf_lo(v.w); acc[8 * i + 7] += bf_hi(v.w);
                    }
                }
                if (sl == 7) {
                    fence_async_smem();
                    nbar_sync(3 + wg, 128);
                    if ((tid & 127) == 0) mbar_arrive(bar_rfree);
                }
                const uint32_t hb = sb + sl * 16384 + (warp * 16 + r) * 128 + t * 4;
#pragma unroll
                for (int j = 0; j < 8; j++) {
                    const uint32_t a = hb + ((j ^ r) << 4);
                    const uint32_t h0 = lds32(a), h1 = lds32(a + 1024);
                    sts32(a, pack_bf16(bf_lo(h0) + st0.rstd * acc[4 * j], bf_hi(h0) + st0.rstd * acc[4 * j + 1]));
                    sts32(a + 1024, pack_bf16(bf_lo(h1) + st1.rstd * acc[4 * j + 2], bf_hi(h1) + st1.rstd * acc[4 * j + 3]));
                }
                fence_async_smem();
                nbar_sync(3 + wg, 128);
                if ((tid & 127) == 0) {
                    tma_store_2d(&tm_out, sb + sl * 16384 + wg * 8192, sl * 64, rb * 128 + wg * 64);
                    bulk_commit();
                }
            }
            if (++sl == 9) sl = 0;
        }
        if ((tid & 127) == 0) bulk_wait_read();
    }
}

typedef CUresult (*EncodeFn)(CUtensorMap*, CUtensorMapDataType, cuuint32_t, void*, const cuuint64_t*, const cuuint64_t*,
                             const cuuint32_t*, const cuuint32_t*, CUtensorMapInterleave, CUtensorMapSwizzle,
                             CUtensorMapL2promotion, CUtensorMapFloatOOBfill);

void make_map(EncodeFn enc, CUtensorMap* m, const void* ptr, int cols, int rows, int box_c, int box_r, int chunks, CUtensorMapSwizzle sw) {
    const cuuint64_t dims[3] = {(cuuint64_t)cols, (cuuint64_t)rows, (cuuint64_t)chunks};
    const cuuint64_t strides[2] = {(cuuint64_t)cols * 2, (cuuint64_t)box_c * 2};
    const cuuint32_t box[3] = {(cuuint32_t)box_c, (cuuint32_t)box_r, (cuuint32_t)chunks};
    const cuuint32_t es[3] = {1, 1, 1};
    enc(m, CU_TENSOR_MAP_DATA_TYPE_BFLOAT16, chunks > 1 ? 3 : 2, (void*)ptr, dims, strides, box, es, CU_TENSOR_MAP_INTERLEAVE_NONE, sw,
        CU_TENSOR_MAP_L2_PROMOTION_NONE, CU_TENSOR_MAP_FLOAT_OOB_FILL_NONE);
}

}

extern "C" void kernel_launch(void* const* d_in, const int* in_sizes, int n_in, void* d_out, int out_size) {
    const __nv_bfloat16* x = (const __nv_bfloat16*)d_in[0];
    const __nv_bfloat16* wqkv = (const __nv_bfloat16*)d_in[1];
    const __nv_bfloat16* wo = (const __nv_bfloat16*)d_in[2];
    const __nv_bfloat16* w1 = (const __nv_bfloat16*)d_in[4];
    const __nv_bfloat16* w2 = (const __nv_bfloat16*)d_in[5];

    void* fn = nullptr;
    cudaDriverEntryPointQueryResult qr;
    cudaGetDriverEntryPoint("cuTensorMapEncodeTiled", &fn, cudaEnableDefault, &qr);
    EncodeFn enc = (EncodeFn)fn;
    void *p_attn = nullptr, *p_h = nullptr;
    cudaGetSymbolAddress(&p_attn, g_attn);
    cudaGetSymbolAddress(&p_h, g_h);
    CUtensorMap tm_x, tm_wqkv, tm_attn, tm_h, tm_w1, tm_w2, tm_out;
    make_map(enc, &tm_x, x, DM, SEQ, 64, 128, 1, CU_TENSOR_MAP_SWIZZLE_128B);
    make_map(enc, &tm_wqkv, wqkv, 1728, DM, 32, 16, 7, CU_TENSOR_MAP_SWIZZLE_64B);
    make_map(enc, &tm_attn, p_attn, DM, SEQ, 64, 64, 1, CU_TENSOR_MAP_SWIZZLE_128B);
    make_map(enc, &tm_h, p_h, DM, SEQ, 64, 128, 1, CU_TENSOR_MAP_SWIZZLE_128B);
    make_map(enc, &tm_w1, w1, FF, DM, 64, 16, 3, CU_TENSOR_MAP_SWIZZLE_128B);
    make_map(enc, &tm_w2, w2, DM, FF, 64, 48, 1, CU_TENSOR_MAP_SWIZZLE_128B);
    make_map(enc, &tm_out, d_out, DM, SEQ, 64, 64, 1, CU_TENSOR_MAP_SWIZZLE_128B);

    cudaFuncSetAttribute(qkv_kernel, cudaFuncAttributeMaxDynamicSharedMemorySize, A_SMEM);
    cudaFuncSetAttribute(attn_kernel, cudaFuncAttributeMaxDynamicSharedMemorySize, B_SMEM);
    cudaFuncSetAttribute(ffn_kernel, cudaFuncAttributeMaxDynamicSharedMemorySize, C_SMEM);

    cudaLaunchAttribute at[2];
    at[0].id = cudaLaunchAttributeClusterDimension;
    at[0].val.clusterDim.x = 2; at[0].val.clusterDim.y = 1; at[0].val.clusterDim.z = 1;
    at[1].id = cudaLaunchAttributeProgrammaticStreamSerialization;
    at[1].val.programmaticStreamSerializationAllowed = 1;

    cudaLaunchConfig_t cfg = {};
    cfg.stream = cudaStreamPerThread;
    cfg.gridDim = 132; cfg.blockDim = A_THREADS; cfg.dynamicSmemBytes = A_SMEM; cfg.attrs = at; cfg.numAttrs = 1;
    cudaLaunchKernelEx(&cfg, qkv_kernel, tm_x, tm_wqkv, x, wqkv, wo);
    cfg.gridDim = 132; cfg.blockDim = 512; cfg.dynamicSmemBytes = B_SMEM; cfg.attrs = at + 1; cfg.numAttrs = 1;
    cudaLaunchKernelEx(&cfg, attn_kernel, w1, w2);
    cfg.gridDim = 128; cfg.blockDim = 384; cfg.dynamicSmemBytes = C_SMEM; cfg.attrs = at; cfg.numAttrs = 2;
    cudaLaunchKernelEx(&cfg, ffn_kernel, tm_attn, tm_h, tm_w1, tm_w2, tm_out, x);
}
```

```cpp
#include <cuda_runtime.h>
#include <cuda_bf16.h>
#include <cuda.h>
#include <stdint.h>
#include <type_traits>

#define PROMO_X CU_TENSOR_MAP_L2_PROMOTION_NONE
#define PROMO_W CU_TENSOR_MAP_L2_PROMOTION_NONE
#define STAGGER -1
#define LAG 2
#ifndef LONG_NS
#define LONG_NS 20u
#endif
#define POLL_SLEEP 0
#define NOMC 0
#define HPACE 2
#define TCT 0
namespace {

constexpr int SEQ = 2048, DM = 576, FF = 4608;
constexpr float LN_EPS = 1e-5f;
constexpr float QSCALE = 0.34004428f;

constexpr int BLK_BYTES = 6144;
constexpr int SLOT_BYTES = 16 * BLK_BYTES;
constexpr uint32_t POLY_PATTERN = 0xB5B5u;

__device__ __align__(1024) uint8_t g_qkv[96 * SLOT_BYTES];
__device__ __align__(1024) __nv_bfloat16 g_attn[SEQ * DM];
__device__ __align__(1024) uint8_t g_h[16 * 147456];
__device__ __align__(1024) uint8_t g_wo_img[8 * 82944];
__device__ __align__(1024) uint8_t g_part[16 * 9 * 8 * 16384];
__device__ __align__(128) float g_cs0[8 * 18 * 216];
__device__ __align__(128) uint8_t g_cs1[FF / 8 * 128];
__device__ __align__(128) float2 g_xstat[SEQ];
__device__ __align__(128) float2 g_hstat[8 * SEQ];
__device__ __align__(16) float g_kmax[8 * 128];
__device__ unsigned int g_cnt_a[32];
constexpr int FLAG_H = 0, FLAG_HST = 256, FLAG_PART = 272, FLAG_WO = FLAG_PART + 16 * 9 * 8, N_FLAG_C = FLAG_WO + 8;
__device__ unsigned int g_flag_c[N_FLAG_C];

#define TL(k, id)
#define TC(k, id)
constexpr uint32_t SPIN_LIMIT = 1u << 18;
#define SUSPEND_NS 20u

__device__ __forceinline__ uint32_t smem_u32(const void* p) { return (uint32_t)__cvta_generic_to_shared(p); }
__device__ __forceinline__ void mbar_init(uint32_t bar, uint32_t cnt) { asm volatile("mbarrier.init.shared::cta.b64 [%0], %1;" :: "r"(bar), "r"(cnt) : "memory"); }
__device__ __forceinline__ void mbar_expect(uint32_t bar, uint32_t bytes) { asm volatile("mbarrier.arrive.expect_tx.shared::cta.b64 _, [%0], %1;" :: "r"(bar), "r"(bytes) : "memory"); }
__device__ __forceinline__ void mbar_arrive(uint32_t bar) { asm volatile("mbarrier.arrive.shared::cta.b64 _, [%0];" :: "r"(bar) : "memory"); }
__device__ __forceinline__ void mbar_arrive_cluster(uint32_t bar) { asm volatile("mbarrier.arrive.shared::cluster.b64 _, [%0];" :: "r"(bar) : "memory"); }
__device__ __forceinline__ void mbar_wait(uint32_t bar, uint32_t parity) {
    asm volatile("{\n.reg .pred p, q;\n.reg .u32 n;\n"
                 "mbarrier.try_wait.parity.shared::cta.b64 p, [%0], %1;\n@p bra.uni WAIT_DONE;\nmov.u32 n, 0;\n"
                 "WAIT_LOOP:\nmbarrier.try_wait.parity.shared::cta.b64 p, [%0], %1;\nadd.u32 n, n, 1;\nsetp.gt.or.u32 q, n, %2, p;\n@!q bra.uni WAIT_LOOP;\n"
                 "WAIT_DONE:\n}\n" :: "r"(bar), "r"(parity), "n"(SPIN_LIMIT) : "memory");
}
__device__ __forceinline__ void mbar_wait_trap(uint32_t bar, uint32_t parity, uint32_t suspend_ns = SUSPEND_NS) {
    for (uint32_t i = 0;; i++) {
        uint32_t ok;
        asm volatile("{\n.reg .pred p;\nmbarrier.try_wait.parity.shared::cta.b64 p, [%1], %2, %3;\nselp.u32 %0, 1, 0, p;\n}\n"
                     : "=r"(ok) : "r"(bar), "r"(parity), "r"(suspend_ns) : "memory");
        if (ok) break;
        if (i > SPIN_LIMIT) __trap();
    }
}
__device__ __forceinline__ uint32_t mapa(uint32_t addr, uint32_t rank) { uint32_t r; asm("mapa.shared::cluster.u32 %0, %1, %2;" : "=r"(r) : "r"(addr), "r"(rank)); return r; }
__device__ __forceinline__ void cluster_sync() { asm volatile("barrier.cluster.arrive.relaxed.aligned;\nbarrier.cluster.wait.aligned;" ::: "memory"); }
__device__ __forceinline__ void fence_mbar_init() { asm volatile("fence.mbarrier_init.release.cluster;" ::: "memory"); }
__device__ __forceinline__ void fence_async_smem() { asm volatile("fence.proxy.async.shared::cta;" ::: "memory"); }
__device__ __forceinline__ void nbar_sync(uint32_t id, uint32_t n) { asm volatile("bar.sync %0, %1;" :: "r"(id), "r"(n) : "memory"); }
__device__ __forceinline__ void nbar_arrive(uint32_t id, uint32_t n) { asm volatile("bar.arrive %0, %1;" :: "r"(id), "r"(n) : "memory"); }
__device__ __forceinline__ void pdl_wait() { asm volatile("griddepcontrol.wait;" ::: "memory"); }
__device__ __forceinline__ void pdl_launch() { asm volatile("griddepcontrol.launch_dependents;" ::: "memory"); }
__device__ __forceinline__ void flag_add(unsigned int* p) { asm volatile("red.relaxed.gpu.global.add.u32 [%0], 1;" :: "l"(p) : "memory"); }
__device__ __forceinline__ void flag_wait(const unsigned int* p, uint32_t target) {
    uint32_t v;
    for (uint32_t i = 0;; i++) {
        asm volatile("ld.acquire.gpu.global.u32 %0, [%1];" : "=r"(v) : "l"(p) : "memory");
        if (v >= target) break;
        if (i > SPIN_LIMIT) __trap();
    }
}
__device__ __forceinline__ uint32_t flag_poll(const unsigned int* p, bool active, uint32_t target) {
    uint32_t v = 0;
    if (active) asm volatile("ld.acquire.gpu.global.u32 %0, [%1];" : "=r"(v) : "l"(p) : "memory");
    return __ballot_sync(~0u, v >= target);
}
__device__ __forceinline__ void flag_wait_soft(const unsigned int* p, uint32_t target) {
    uint32_t v;
    for (uint32_t i = 0; i < SPIN_LIMIT; i++) {
        asm volatile("ld.acquire.gpu.global.u32 %0, [%1];" : "=r"(v) : "l"(p) : "memory");
        if (v >= target) break;
    }
}
__device__ __forceinline__ void bulk_load(uint32_t dst, const void* src, uint32_t bytes, uint32_t bar) {
    asm volatile("cp.async.bulk.shared::cluster.global.mbarrier::complete_tx::bytes [%0], [%1], %2, [%3];" :: "r"(dst), "l"(src), "r"(bytes), "r"(bar) : "memory");
}
__device__ __forceinline__ void bulk_store(void* dst, uint32_t src, uint32_t bytes) {
    asm volatile("cp.async.bulk.global.shared::cta.bulk_group [%0], [%1], %2;" :: "l"(dst), "r"(src), "r"(bytes) : "memory");
}
__device__ __forceinline__ void bulk_commit() { asm volatile("cp.async.bulk.commit_group;" ::: "memory"); }
__device__ __forceinline__ void bulk_wait_all() { asm volatile("cp.async.bulk.wait_group 0;" ::: "memory"); }
__device__ __forceinline__ void bulk_wait_read() { asm volatile("cp.async.bulk.wait_group.read 0;" ::: "memory"); }
__device__ __forceinline__ void l2_prefetch(const void* src, uint32_t bytes) { asm volatile("cp.async.bulk.prefetch.L2.global [%0], %1;" :: "l"(src), "r"(bytes) : "memory"); }
__device__ __forceinline__ void tma_2d(uint32_t dst, const CUtensorMap* m, int c0, int c1, uint32_t bar) {
    asm volatile("cp.async.bulk.tensor.2d.shared::cluster.global.mbarrier::complete_tx::bytes [%0], [%1, {%3, %4}], [%2];"
                 :: "r"(dst), "l"(m), "r"(bar), "r"(c0), "r"(c1) : "memory");
}
__device__ __forceinline__ void tma_2d_mc(uint32_t dst, const CUtensorMap* m, int c0, int c1, uint32_t bar) {
    asm volatile("cp.async.bulk.tensor.2d.shared::cluster.global.mbarrier::complete_tx::bytes.multicast::cluster [%0], [%1, {%3, %4}], [%2], %5;"
                 :: "r"(dst), "l"(m), "r"(bar), "r"(c0), "r"(c1), "h"((uint16_t)3) : "memory");
}
__device__ __forceinline__ void tma_3d(uint32_t dst, const CUtensorMap* m, int c0, int c1, uint32_t bar) {
    asm volatile("cp.async.bulk.tensor.3d.shared::cluster.global.mbarrier::complete_tx::bytes [%0], [%1, {%3, %4, %5}], [%2];"
                 :: "r"(dst), "l"(m), "r"(bar), "r"(c0), "r"(c1), "r"(0) : "memory");
}
__device__ __forceinline__ void tma_3d_mc(uint32_t dst, const CUtensorMap* m, int c0, int c1, uint32_t bar) {
    asm volatile("cp.async.bulk.tensor.3d.shared::cluster.global.mbarrier::complete_tx::bytes.multicast::cluster [%0], [%1, {%3, %4, %5}], [%2], %6;"
                 :: "r"(dst), "l"(m), "r"(bar), "r"(c0), "r"(c1), "r"(0), "h"((uint16_t)3) : "memory");
}
__device__ __forceinline__ void tma_store_2d(const CUtensorMap* m, uint32_t src, int c0, int c1) {
    asm volatile("cp.async.bulk.tensor.2d.global.shared::cta.bulk_group [%0, {%2, %3}], [%1];" :: "l"(m), "r"(src), "r"(c0), "r"(c1) : "memory");
}
__device__ __forceinline__ void tma_prefetch_desc(const CUtensorMap* m) { asm volatile("prefetch.tensormap [%0];" :: "l"(m) : "memory"); }
__device__ __forceinline__ void wg_fence() { asm volatile("wgmma.fence.sync.aligned;" ::: "memory"); }
__device__ __forceinline__ void wg_commit() { asm volatile("wgmma.commit_group.sync.aligned;" ::: "memory"); }
template <int N> __device__ __forceinline__ void wg_wait() { asm volatile("wgmma.wait_group.sync.aligned %0;" :: "n"(N) : "memory"); }
template <int N> __device__ __forceinline__ void fence_regs(float (&d)[N]) {
#pragma unroll
    for (int i = 0; i < N; i++) asm volatile("" : "+f"(d[i]) :: "memory");
}
template <int N> __device__ __forceinline__ void fence_regs(uint32_t (&d)[N]) {
#pragma unroll
    for (int i = 0; i < N; i++) asm volatile("" : "+r"(d[i]) :: "memory");
}
__device__ __forceinline__ uint32_t pack_bf16(float lo, float hi) { uint32_t r; asm("cvt.rn.bf16x2.f32 %0, %1, %2;" : "=r"(r) : "f"(hi), "f"(lo)); return r; }
__device__ __forceinline__ uint32_t pack_bf16_relu(float lo, float hi) { uint32_t r; asm("cvt.rn.relu.bf16x2.f32 %0, %1, %2;" : "=r"(r) : "f"(hi), "f"(lo)); return r; }
__device__ __forceinline__ float bf_lo(uint32_t w) { return __uint_as_float(w << 16); }
__device__ __forceinline__ float bf_hi(uint32_t w) { return __uint_as_float(w & 0xFFFF0000u); }
__device__ __forceinline__ float ex2(float x) { float r; asm("ex2.approx.ftz.f32 %0, %1;" : "=f"(r) : "f"(x)); return r; }
__device__ __forceinline__ void sts32(uint32_t a, uint32_t v) { asm volatile("st.shared.b32 [%0], %1;" :: "r"(a), "r"(v) : "memory"); }
__device__ __forceinline__ void sts64f(uint32_t a, float x, float y) { asm volatile("st.shared.v2.f32 [%0], {%1, %2};" :: "r"(a), "f"(x), "f"(y) : "memory"); }
__device__ __forceinline__ void sts128(uint32_t a, uint32_t x, uint32_t y, uint32_t z, uint32_t w) { asm volatile("st.shared.v4.b32 [%0], {%1, %2, %3, %4};" :: "r"(a), "r"(x), "r"(y), "r"(z), "r"(w) : "memory"); }
__device__ __forceinline__ uint32_t lds32(uint32_t a) { uint32_t v; asm volatile("ld.shared.b32 %0, [%1];" : "=r"(v) : "r"(a) : "memory"); return v; }
__device__ __forceinline__ float2 lds64f(uint32_t a) { float2 v; asm volatile("ld.shared.v2.f32 {%0, %1}, [%2];" : "=f"(v.x), "=f"(v.y) : "r"(a) : "memory"); return v; }
__device__ __forceinline__ uint4 lds128(uint32_t a) { uint4 v; asm volatile("ld.shared.v4.b32 {%0, %1, %2, %3}, [%4];" : "=r"(v.x), "=r"(v.y), "=r"(v.z), "=r"(v.w) : "r"(a) : "memory"); return v; }

__device__ __forceinline__ uint32_t desc_addr(uint32_t a) { return (a & 0x3FFFFu) >> 4; }
constexpr uint32_t HI_SW128 = (1024 >> 4) | (1u << 30);
constexpr uint32_t HI_SW64 = (512 >> 4) | (2u << 30);

__device__ __forceinline__ void mma_ss_n224(float (&d)[112], uint32_t alo, uint32_t ahi, uint32_t blo, uint32_t bhi, uint32_t acc) {
    asm volatile("{\n.reg .b64 da, db;\n.reg .pred p;\nsetp.ne.u32 p, %116, 0;\nmov.b64 da, {%112, %113};\nmov.b64 db, {%114, %115};\n"
        "wgmma.mma_async.sync.aligned.m64n224k16.f32.bf16.bf16 "
        "{%0, %1, %2, %3, %4, %5, %6, %7, %8, %9, %10, %11, %12, %13, %14, %15, "
        "%16, %17, %18, %19, %20, %21, %22, %23, %24, %25, %26, %27, %28, %29, %30, %31, "
        "%32, %33, %34, %35, %36, %37, %38, %39, %40, %41, %42, %43, %44, %45, %46, %47, "
        "%48, %49, %50, %51, %52, %53, %54, %55, %56, %57, %58, %59, %60, %61, %62, %63, "
        "%64, %65, %66, %67, %68, %69, %70, %71, %72, %73, %74, %75, %76, %77, %78, %79, "
        "%80, %81, %82, %83, %84, %85, %86, %87, %88, %89, %90, %91, %92, %93, %94, %95, "
        "%96, %97, %98, %99, %100, %101, %102, %103, %104, %105, %106, %107, %108, %109, %110, %111}, "
        "da, db, p, 1, 1, 0, 1;\n}\n"
        : "+f"(d[0]), "+f"(d[1]), "+f"(d[2]), "+f"(d[3]), "+f"(d[4]), "+f"(d[5]), "+f"(d[6]), "+f"(d[7]),
          "+f"(d[8]), "+f"(d[9]), "+f"(d[10]), "+f"(d[11]), "+f"(d[12]), "+f"(d[13]), "+f"(d[14]), "+f"(d[15]),
          "+f"(d[16]), "+f"(d[17]), "+f"(d[18]), "+f"(d[19]), "+f"(d[20]), "+f"(d[21]), "+f"(d[22]), "+f"(d[23]),
          "+f"(d[24]), "+f"(d[25]), "+f"(d[26]), "+f"(d[27]), "+f"(d[28]), "+f"(d[29]), "+f"(d[30]), "+f"(d[31]),
          "+f"(d[32]), "+f"(d[33]), "+f"(d[34]), "+f"(d[35]), "+f"(d[36]), "+f"(d[37]), "+f"(d[38]), "+f"(d[39]),
          "+f"(d[40]), "+f"(d[41]), "+f"(d[42]), "+f"(d[43]), "+f"(d[44]), "+f"(d[45]), "+f"(d[46]), "+f"(d[47]),
          "+f"(d[48]), "+f"(d[49]), "+f"(d[50]), "+f"(d[51]), "+f"(d[52]), "+f"(d[53]), "+f"(d[54]), "+f"(d[55]),
          "+f"(d[56]), "+f"(d[57]), "+f"(d[58]), "+f"(d[59]), "+f"(d[60]), "+f"(d[61]), "+f"(d[62]), "+f"(d[63]),
          "+f"(d[64]), "+f"(d[65]), "+f"(d[66]), "+f"(d[67]), "+f"(d[68]), "+f"(d[69]), "+f"(d[70]), "+f"(d[71]),
          "+f"(d[72]), "+f"(d[73]), "+f"(d[74]), "+f"(d[75]), "+f"(d[76]), "+f"(d[77]), "+f"(d[78]), "+f"(d[79]),
          "+f"(d[80]), "+f"(d[81]), "+f"(d[82]), "+f"(d[83]), "+f"(d[84]), "+f"(d[85]), "+f"(d[86]), "+f"(d[87]),
          "+f"(d[88]), "+f"(d[89]), "+f"(d[90]), "+f"(d[91]), "+f"(d[92]), "+f"(d[93]), "+f"(d[94]), "+f"(d[95]),
          "+f"(d[96]), "+f"(d[97]), "+f"(d[98]), "+f"(d[99]), "+f"(d[100]), "+f"(d[101]), "+f"(d[102]), "+f"(d[103]),
          "+f"(d[104]), "+f"(d[105]), "+f"(d[106]), "+f"(d[107]), "+f"(d[108]), "+f"(d[109]), "+f"(d[110]), "+f"(d[111])
        : "r"(alo), "r"(ahi), "r"(blo), "r"(bhi), "r"(acc));
}
__device__ __forceinline__ void mma_qk_first(float (&d)[32], uint32_t a0, uint32_t a1, uint32_t a2, uint32_t a3, uint64_t db) {
    asm volatile("wgmma.mma_async.sync.aligned.m64n64k16.f32.bf16.bf16 "
        "{%0, %1, %2, %3, %4, %5, %6, %7, %8, %9, %10, %11, %12, %13, %14, %15, "
        "%16, %17, %18, %19, %20, %21, %22, %23, %24, %25, %26, %27, %28, %29, %30, %31}, "
        "{%32, %33, %34, %35}, %36, 0, 1, 1, 0;"
        : "=f"(d[0]), "=f"(d[1]), "=f"(d[2]), "=f"(d[3]), "=f"(d[4]), "=f"(d[5]), "=f"(d[6]), "=f"(d[7]),
          "=f"(d[8]), "=f"(d[9]), "=f"(d[10]), "=f"(d[11]), "=f"(d[12]), "=f"(d[13]), "=f"(d[14]), "=f"(d[15]),
          "=f"(d[16]), "=f"(d[17]), "=f"(d[18]), "=f"(d[19]), "=f"(d[20]), "=f"(d[21]), "=f"(d[22]), "=f"(d[23]),
          "=f"(d[24]), "=f"(d[25]), "=f"(d[26]), "=f"(d[27]), "=f"(d[28]), "=f"(d[29]), "=f"(d[30]), "=f"(d[31])
        : "r"(a0), "r"(a1), "r"(a2), "r"(a3), "l"(db));
}
__device__ __forceinline__ void mma_qk_second(float (&d)[32], uint32_t a0, uint32_t a1, uint32_t a2, uint32_t a3, uint64_t db) {
    asm volatile("wgmma.mma_async.sync.aligned.m64n64k16.f32.bf16.bf16 "
        "{%0, %1, %2, %3, %4, %5, %6, %7, %8, %9, %10, %11, %12, %13, %14, %15, "
        "%16, %17, %18, %19, %20, %21, %22, %23, %24, %25, %26, %27, %28, %29, %30, %31}, "
        "{%32, %33, %34, %35}, %36, 1, 1, 1, 0;"
        : "+f"(d[0]), "+f"(d[1]), "+f"(d[2]), "+f"(d[3]), "+f"(d[4]), "+f"(d[5]), "+f"(d[6]), "+f"(d[7]),
          "+f"(d[8]), "+f"(d[9]), "+f"(d[10]), "+f"(d[11]), "+f"(d[12]), "+f"(d[13]), "+f"(d[14]), "+f"(d[15]),
          "+f"(d[16]), "+f"(d[17]), "+f"(d[18]), "+f"(d[19]), "+f"(d[20]), "+f"(d[21]), "+f"(d[22]), "+f"(d[23]),
          "+f"(d[24]), "+f"(d[25]), "+f"(d[26]), "+f"(d[27]), "+f"(d[28]), "+f"(d[29]), "+f"(d[30]), "+f"(d[31])
        : "r"(a0), "r"(a1), "r"(a2), "r"(a3), "l"(db));
}
__device__ __forceinline__ void mma_pv(float (&d)[12], uint32_t a0, uint32_t a1, uint32_t a2, uint32_t a3, uint64_t db) {
    asm volatile("wgmma.mma_async.sync.aligned.m64n24k16.f32.bf16.bf16 "
        "{%0, %1, %2, %3, %4, %5, %6, %7, %8, %9, %10, %11}, "
        "{%12, %13, %14, %15}, %16, 1, 1, 1, 1;"
        : "+f"(d[0]), "+f"(d[1]), "+f"(d[2]), "+f"(d[3]), "+f"(d[4]), "+f"(d[5]), "+f"(d[6]), "+f"(d[7]),
          "+f"(d[8]), "+f"(d[9]), "+f"(d[10]), "+f"(d[11])
        : "r"(a0), "r"(a1), "r"(a2), "r"(a3), "l"(db));
}
__device__ __forceinline__ void mma_ss_n72(float (&d)[36], uint32_t alo, uint32_t ahi, uint32_t blo, uint32_t bhi, uint32_t acc) {
    asm volatile("{\n.reg .b64 da, db;\n.reg .pred p;\nsetp.ne.u32 p, %40, 0;\nmov.b64 da, {%36, %37};\nmov.b64 db, {%38, %39};\n"
        "wgmma.mma_async.sync.aligned.m64n72k16.f32.bf16.bf16 "
        "{%0, %1, %2, %3, %4, %5, %6, %7, %8, %9, %10, %11, %12, %13, %14, %15, "
        "%16, %17, %18, %19, %20, %21, %22, %23, %24, %25, %26, %27, %28, %29, %30, %31, "
        "%32, %33, %34, %35}, "
        "da, db, p, 1, 1, 0, 1;\n}\n"
        : "+f"(d[0]), "+f"(d[1]), "+f"(d[2]), "+f"(d[3]), "+f"(d[4]), "+f"(d[5]), "+f"(d[6]), "+f"(d[7]),
          "+f"(d[8]), "+f"(d[9]), "+f"(d[10]), "+f"(d[11]), "+f"(d[12]), "+f"(d[13]), "+f"(d[14]), "+f"(d[15]),
          "+f"(d[16]), "+f"(d[17]), "+f"(d[18]), "+f"(d[19]), "+f"(d[20]), "+f"(d[21]), "+f"(d[22]), "+f"(d[23]),
          "+f"(d[24]), "+f"(d[25]), "+f"(d[26]), "+f"(d[27]), "+f"(d[28]), "+f"(d[29]), "+f"(d[30]), "+f"(d[31]),
          "+f"(d[32]), "+f"(d[33]), "+f"(d[34]), "+f"(d[35])
        : "r"(alo), "r"(ahi), "r"(blo), "r"(bhi), "r"(acc));
}
__device__ __forceinline__ void mma_ss_n192(float (&d)[96], uint32_t alo, uint32_t ahi, uint32_t blo, uint32_t bhi, uint32_t acc) {
    asm volatile("{\n.reg .b64 da, db;\n.reg .pred p;\nsetp.ne.u32 p, %100, 0;\nmov.b64 da, {%96, %97};\nmov.b64 db, {%98, %99};\n"
        "wgmma.mma_async.sync.aligned.m64n192k16.f32.bf16.bf16 "
        "{%0, %1, %2, %3, %4, %5, %6, %7, %8, %9, %10, %11, %12, %13, %14, %15, "
        "%16, %17, %18, %19, %20, %21, %22, %23, %24, %25, %26, %27, %28, %29, %30, %31, "
        "%32, %33, %34, %35, %36, %37, %38, %39, %40, %41, %42, %43, %44, %45, %46, %47, "
        "%48, %49, %50, %51, %52, %53, %54, %55, %56, %57, %58, %59, %60, %61, %62, %63, "
        "%64, %65, %66, %67, %68, %69, %70, %71, %72, %73, %74, %75, %76, %77, %78, %79, "
        "%80, %81, %82, %83, %84, %85, %86, %87, %88, %89, %90, %91, %92, %93, %94, %95}, "
        "da, db, p, 1, 1, 0, 1;\n}\n"
        : "+f"(d[0]), "+f"(d[1]), "+f"(d[2]), "+f"(d[3]), "+f"(d[4]), "+f"(d[5]), "+f"(d[6]), "+f"(d[7]),
          "+f"(d[8]), "+f"(d[9]), "+f"(d[10]), "+f"(d[11]), "+f"(d[12]), "+f"(d[13]), "+f"(d[14]), "+f"(d[15]),
          "+f"(d[16]), "+f"(d[17]), "+f"(d[18]), "+f"(d[19]), "+f"(d[20]), "+f"(d[21]), "+f"(d[22]), "+f"(d[23]),
          "+f"(d[24]), "+f"(d[25]), "+f"(d[26]), "+f"(d[27]), "+f"(d[28]), "+f"(d[29]), "+f"(d[30]), "+f"(d[31]),
          "+f"(d[32]), "+f"(d[33]), "+f"(d[34]), "+f"(d[35]), "+f"(d[36]), "+f"(d[37]), "+f"(d[38]), "+f"(d[39]),
          "+f"(d[40]), "+f"(d[41]), "+f"(d[42]), "+f"(d[43]), "+f"(d[44]), "+f"(d[45]), "+f"(d[46]), "+f"(d[47]),
          "+f"(d[48]), "+f"(d[49]), "+f"(d[50]), "+f"(d[51]), "+f"(d[52]), "+f"(d[53]), "+f"(d[54]), "+f"(d[55]),
          "+f"(d[56]), "+f"(d[57]), "+f"(d[58]), "+f"(d[59]), "+f"(d[60]), "+f"(d[61]), "+f"(d[62]), "+f"(d[63]),
          "+f"(d[64]), "+f"(d[65]), "+f"(d[66]), "+f"(d[67]), "+f"(d[68]), "+f"(d[69]), "+f"(d[70]), "+f"(d[71]),
          "+f"(d[72]), "+f"(d[73]), "+f"(d[74]), "+f"(d[75]), "+f"(d[76]), "+f"(d[77]), "+f"(d[78]), "+f"(d[79]),
          "+f"(d[80]), "+f"(d[81]), "+f"(d[82]), "+f"(d[83]), "+f"(d[84]), "+f"(d[85]), "+f"(d[86]), "+f"(d[87]),
          "+f"(d[88]), "+f"(d[89]), "+f"(d[90]), "+f"(d[91]), "+f"(d[92]), "+f"(d[93]), "+f"(d[94]), "+f"(d[95])
        : "r"(alo), "r"(ahi), "r"(blo), "r"(bhi), "r"(acc));
}
__device__ __forceinline__ void mma_rs_n64(float (&d)[32], uint32_t a0, uint32_t a1, uint32_t a2, uint32_t a3, uint32_t blo, uint32_t bhi, uint32_t acc) {
    asm volatile("{\n.reg .b64 da, db;\n.reg .pred p;\nsetp.ne.u32 p, %38, 0;\nmov.b64 db, {%36, %37};\n"
        "wgmma.mma_async.sync.aligned.m64n64k16.f32.bf16.bf16 "
        "{%0, %1, %2, %3, %4, %5, %6, %7, %8, %9, %10, %11, %12, %13, %14, %15, "
        "%16, %17, %18, %19, %20, %21, %22, %23, %24, %25, %26, %27, %28, %29, %30, %31}, "
        "{%32, %33, %34, %35}, db, p, 1, 1, 1;\n}\n"
        : "+f"(d[0]), "+f"(d[1]), "+f"(d[2]), "+f"(d[3]), "+f"(d[4]), "+f"(d[5]), "+f"(d[6]), "+f"(d[7]),
          "+f"(d[8]), "+f"(d[9]), "+f"(d[10]), "+f"(d[11]), "+f"(d[12]), "+f"(d[13]), "+f"(d[14]), "+f"(d[15]),
          "+f"(d[16]), "+f"(d[17]), "+f"(d[18]), "+f"(d[19]), "+f"(d[20]), "+f"(d[21]), "+f"(d[22]), "+f"(d[23]),
          "+f"(d[24]), "+f"(d[25]), "+f"(d[26]), "+f"(d[27]), "+f"(d[28]), "+f"(d[29]), "+f"(d[30]), "+f"(d[31])
        : "r"(a0), "r"(a1), "r"(a2), "r"(a3), "r"(blo), "r"(bhi), "r"(acc));
}
__device__ __forceinline__ void mma_rs_n192(float (&d)[96], uint32_t a0, uint32_t a1, uint32_t a2, uint32_t a3, uint32_t blo, uint32_t bhi) {
    asm volatile("{\n.reg .b64 da, db;\nmov.b64 db, {%100, %101};\n"
        "wgmma.mma_async.sync.aligned.m64n192k16.f32.bf16.bf16 "
        "{%0, %1, %2, %3, %4, %5, %6, %7, %8, %9, %10, %11, %12, %13, %14, %15, "
        "%16, %17, %18, %19, %20, %21, %22, %23, %24, %25, %26, %27, %28, %29, %30, %31, "
        "%32, %33, %34, %35, %36, %37, %38, %39, %40, %41, %42, %43, %44, %45, %46, %47, "
        "%48, %49, %50, %51, %52, %53, %54, %55, %56, %57, %58, %59, %60, %61, %62, %63, "
        "%64, %65, %66, %67, %68, %69, %70, %71, %72, %73, %74, %75, %76, %77, %78, %79, "
        "%80, %81, %82, %83, %84, %85, %86, %87, %88, %89, %90, %91, %92, %93, %94, %95}, "
        "{%96, %97, %98, %99}, db, 1, 1, 1, 1;\n}\n"
        : "+f"(d[0]), "+f"(d[1]), "+f"(d[2]), "+f"(d[3]), "+f"(d[4]), "+f"(d[5]), "+f"(d[6]), "+f"(d[7]),
          "+f"(d[8]), "+f"(d[9]), "+f"(d[10]), "+f"(d[11]), "+f"(d[12]), "+f"(d[13]), "+f"(d[14]), "+f"(d[15]),
          "+f"(d[16]), "+f"(d[17]), "+f"(d[18]), "+f"(d[19]), "+f"(d[20]), "+f"(d[21]), "+f"(d[22]), "+f"(d[23]),
          "+f"(d[24]), "+f"(d[25]), "+f"(d[26]), "+f"(d[27]), "+f"(d[28]), "+f"(d[29]), "+f"(d[30]), "+f"(d[31]),
          "+f"(d[32]), "+f"(d[33]), "+f"(d[34]), "+f"(d[35]), "+f"(d[36]), "+f"(d[37]), "+f"(d[38]), "+f"(d[39]),
          "+f"(d[40]), "+f"(d[41]), "+f"(d[42]), "+f"(d[43]), "+f"(d[44]), "+f"(d[45]), "+f"(d[46]), "+f"(d[47]),
          "+f"(d[48]), "+f"(d[49]), "+f"(d[50]), "+f"(d[51]), "+f"(d[52]), "+f"(d[53]), "+f"(d[54]), "+f"(d[55]),
          "+f"(d[56]), "+f"(d[57]), "+f"(d[58]), "+f"(d[59]), "+f"(d[60]), "+f"(d[61]), "+f"(d[62]), "+f"(d[63]),
          "+f"(d[64]), "+f"(d[65]), "+f"(d[66]), "+f"(d[67]), "+f"(d[68]), "+f"(d[69]), "+f"(d[70]), "+f"(d[71]),
          "+f"(d[72]), "+f"(d[73]), "+f"(d[74]), "+f"(d[75]), "+f"(d[76]), "+f"(d[77]), "+f"(d[78]), "+f"(d[79]),
          "+f"(d[80]), "+f"(d[81]), "+f"(d[82]), "+f"(d[83]), "+f"(d[84]), "+f"(d[85]), "+f"(d[86]), "+f"(d[87]),
          "+f"(d[88]), "+f"(d[89]), "+f"(d[90]), "+f"(d[91]), "+f"(d[92]), "+f"(d[93]), "+f"(d[94]), "+f"(d[95])
        : "r"(a0), "r"(a1), "r"(a2), "r"(a3), "r"(blo), "r"(bhi));
}
__device__ __forceinline__ void mma_ss_n64(float (&d)[32], uint32_t alo, uint32_t ahi, uint32_t blo, uint32_t bhi) {
    asm volatile("{\n.reg .b64 da, db;\nmov.b64 da, {%32, %33};\nmov.b64 db, {%34, %35};\n"
        "wgmma.mma_async.sync.aligned.m64n64k16.f32.bf16.bf16 "
        "{%0, %1, %2, %3, %4, %5, %6, %7, %8, %9, %10, %11, %12, %13, %14, %15, "
        "%16, %17, %18, %19, %20, %21, %22, %23, %24, %25, %26, %27, %28, %29, %30, %31}, "
        "da, db, 1, 1, 1, 0, 1;\n}\n"
        : "+f"(d[0]), "+f"(d[1]), "+f"(d[2]), "+f"(d[3]), "+f"(d[4]), "+f"(d[5]), "+f"(d[6]), "+f"(d[7]),
          "+f"(d[8]), "+f"(d[9]), "+f"(d[10]), "+f"(d[11]), "+f"(d[12]), "+f"(d[13]), "+f"(d[14]), "+f"(d[15]),
          "+f"(d[16]), "+f"(d[17]), "+f"(d[18]), "+f"(d[19]), "+f"(d[20]), "+f"(d[21]), "+f"(d[22]), "+f"(d[23]),
          "+f"(d[24]), "+f"(d[25]), "+f"(d[26]), "+f"(d[27]), "+f"(d[28]), "+f"(d[29]), "+f"(d[30]), "+f"(d[31])
        : "r"(alo), "r"(ahi), "r"(blo), "r"(bhi));
}

constexpr int A_STAGES = 11;
constexpr uint32_t A_STAGE_BYTES = 14336;
constexpr uint32_t A_OFF_X = A_STAGES * A_STAGE_BYTES;
constexpr uint32_t A_OFF_STG = 7 * A_STAGE_BYTES;
constexpr uint32_t A_OFF_MISC = A_OFF_X + 4 * 16384;
constexpr uint32_t A_SMEM = A_OFF_MISC + 512 + 4096 + 1024;
__device__ __forceinline__ uint32_t x_slot(int kc) { return A_OFF_X + ((kc + 3) & 3) * 16384; }

__device__ __forceinline__ uint32_t absmax_bf16x2(uint32_t m, uint32_t a) {
    uint32_t r;
    asm volatile("max.xorsign.abs.bf16x2 %0, %1, %2;" : "=r"(r) : "r"(m), "r"(a));
    return r;
}

template <int ODD>
__device__ __forceinline__ void qkv_epilogue(const float (&acc)[112], uint32_t sb, uint32_t s_cs, uint32_t bar_out, float2 st0, float2 st1, int ct, int rb, int warp, int lane) {
    const int t = lane & 3;
    uint32_t w[54], vmax = 0, addr[9], gs = 0;
#pragma unroll
    for (int p = 0; p < 3; p++) {
        float2 cs[9];
#pragma unroll
        for (int j = 0; j < 9; j++) cs[j] = lds64f(s_cs + 32 * (9 * p + j + ODD) + 8 * t);
        if (p == 0 || (p == 1 && ct == 5)) {
            const bool isv = ct * 3 + p >= 16;
            gs = isv ? 384u : 128u;
#pragma unroll
            for (int j = 0; j < 9; j++) {
                const int c = 8 * j + 2 * t, slot = c / 18, d0 = c - slot * 18;
                const int d = isv && d0 < 16 ? ((d0 & 2) << 2) | ((d0 >> 2) << 1) : d0;
                addr[j] = sb + (lane >> 2) * 16 + warp * 2 * gs + slot * BLK_BYTES + (d & 7) * 2 + (d >> 3) * (isv ? 128u : 2048u);
            }
        }
        const float sc = ct * 3 + p < 8 ? QSCALE : 1.f;
        const float f0 = st0.y * sc, f1 = st1.y * sc;
#pragma unroll
        for (int j = 0; j < 9; j++) {
            const float* a = &acc[4 * (9 * p + j + ODD)];
            w[18 * p + 2 * j] = pack_bf16((a[0] - st0.x * cs[j].x) * f0, (a[1] - st0.x * cs[j].y) * f0);
            w[18 * p + 2 * j + 1] = pack_bf16((a[2] - st1.x * cs[j].x) * f1, (a[3] - st1.x * cs[j].y) * f1);
            sts32(addr[j] + p * 4 * BLK_BYTES, w[18 * p + 2 * j]);
            sts32(addr[j] + gs + p * 4 * BLK_BYTES, w[18 * p + 2 * j + 1]);
        }
        __syncwarp();
        if (lane == 0) mbar_arrive(bar_out + 8 * p);
        if (warp == 0 && lane == 0) TC(0, 23 + p);
    }
    if (ct < 2) return;
#pragma unroll
    for (int i = 0; i < 54; i++) vmax = absmax_bf16x2(vmax, w[i]);
    float m = fmaxf(fabsf(bf_lo(vmax)), fabsf(bf_hi(vmax)));
#pragma unroll
    for (int o = 16; o > 0; o >>= 1) m = fmaxf(m, __shfl_xor_sync(~0u, m, o));
    if (lane == 0) g_kmax[ct * 128 + rb * 8 + warp] = m;
}

__device__ __forceinline__ void stage_colsum(uint32_t stage, uint32_t bar_wait, uint32_t bar_done, uint32_t dst, int odd, int lane) {
    const int u = (lane < 27 ? lane : 0) + odd;
    uint4 v[32];
    mbar_wait_trap(bar_wait, 0);
#pragma unroll
    for (int k = 0; k < 32; k++) v[k] = lds128(stage + (k >> 4) * 7168 + (u >> 2) * 1024 + (k & 15) * 64 + (((u & 3) ^ ((k >> 1) & 3)) << 4));
    float c = __uint_as_float(v[31].w & 0u);
    __syncwarp();
    if (lane == 0) mbar_arrive(bar_done);
#pragma unroll
    for (int j = 0; j < 8; j++) {
        c *= 0.f;
#pragma unroll
        for (int k = 0; k < 32; k++) {
            const uint32_t w = j < 2 ? v[k].x : j < 4 ? v[k].y : j < 6 ? v[k].z : v[k].w;
            c += (j & 1) ? bf_hi(w) : bf_lo(w);
        }
        if (lane < 27) sts32(dst + lane * 32 + j * 4, __float_as_uint(c));
    }
}

__global__ void __launch_bounds__(384, 1)
qkv_kernel(const __grid_constant__ CUtensorMap tm_x, const __grid_constant__ CUtensorMap tm_w, const __nv_bfloat16* __restrict__ x) {
    extern __shared__ uint8_t smem_raw[];
    const int tid = threadIdx.x, warp = __shfl_sync(~0u, tid >> 5, 0), lane = tid & 31;
    pdl_launch();
    if (tid == 0) { TL(0, 0); TC(0, 0); }
    const uint32_t sb = (smem_u32(smem_raw) + 1023u) & ~1023u;
    const uint32_t bar_a = sb + A_OFF_MISC, bar_full = bar_a + 72, bar_st = bar_full + 88, bar_empty = bar_st + 8, bar_xfree = bar_empty + 56;
    const uint32_t bar_dead = bar_xfree + 40, bar_cdone = bar_dead + 8, bar_out = bar_cdone + 8;
    const uint32_t s_cs = sb + A_OFF_MISC + 512, s_st = s_cs + 1024, s_red = s_st + 1024;
    const int rb = blockIdx.x & 15, ct = blockIdx.x >> 4;
    const uint32_t rank = blockIdx.x & 1;
    const int col0 = 216 * ct - 8 * (ct & 1);
    const int krot = rb >> 1;

    if (lane == 0) {
        mbar_init(bar_a + 8 * warp, 1);
        mbar_init(bar_a + 8 * (warp + 12), warp < 9 ? 1 : 4);
        if (warp < 11) mbar_init(bar_a + 8 * (warp + 24), warp < 4 ? 4 : 2);
        if (warp >= 2 && warp < 5) mbar_init(bar_out + 8 * (warp - 2), 8);
        fence_mbar_init();
        if (warp < 2) {
            mbar_expect(bar_a + 8 * warp, 16384);
            tma_2d(sb + x_slot(warp), &tm_x, (krot + warp) * 64, rb * 128, bar_a + 8 * warp);
        } else if (warp == 9 || warp == 10) {
            const int s = warp - 9;
            mbar_expect(bar_full + 8 * s, A_STAGE_BYTES);
            tma_3d(sb + s * A_STAGE_BYTES, &tm_w, col0, krot * 64 + s * 32, bar_full + 8 * s);
            tma_3d(sb + s * A_STAGE_BYTES + 7168, &tm_w, col0, krot * 64 + s * 32 + 16, bar_full + 8 * s);
        }
    }
    __syncwarp();
    cluster_sync();

    if (warp == 8) {
        if (lane == 0) {
#pragma unroll 1
            for (int s = 2; s < 21; s++) {
                const int kc = s < 5 ? (s >> 1) + 1 : (s >> 1) - 2;
                if (!(s & 1) && (s < 5 || s > 11)) {
                    if (kc >= 4) mbar_wait_trap(bar_xfree + 8 * (kc - 4), 0);
                    mbar_expect(bar_a + 8 * kc, 16384);
                    tma_2d(sb + x_slot(kc), &tm_x, (krot + kc >= 9 ? krot + kc - 9 : krot + kc) * 64, rb * 128, bar_a + 8 * kc);
                }
                if (s < 18) {
                    const int slot = s >= A_STAGES ? s - A_STAGES : s;
                    if (s >= A_STAGES) mbar_wait_trap(bar_empty + 8 * slot, 0);
                    TC(0, 32 + s);
                    int k = krot * 64 + s * 32;
                    if (k >= DM) k -= DM;
                    mbar_expect(bar_full + 8 * slot, A_STAGE_BYTES);
                    tma_3d_mc(sb + slot * A_STAGE_BYTES + rank * 7168, &tm_w, col0, k + rank * 16, bar_full + 8 * slot);
                }
            }
        }
        __syncwarp();
        if (lane < 4) {
#pragma unroll 1
            for (int p = 0; p < 3; p++) {
                mbar_wait_trap(bar_out + 8 * p, 0);
                fence_async_smem();
                bulk_store(g_qkv + (size_t)(ct * 12 + 4 * p + lane) * SLOT_BYTES + rb * BLK_BYTES, sb + A_OFF_STG + (4 * p + lane) * BLK_BYTES, BLK_BYTES);
                bulk_commit();
                if (lane == 0) TC(0, 26 + p);
            }
            if (lane == 0) TL(0, 4);
            bulk_wait_read();
            if (lane == 0) { TL(0, 5); TC(0, 29); }
        }
    } else if (warp > 8) {
        if (warp == 9) {
            stage_colsum(sb + rank * A_STAGE_BYTES, bar_full + 8 * rank, bar_cdone, s_red, ct & 1, lane);
            fence_async_smem();
            nbar_sync(7, 64);
            if (lane == 0) {
                bulk_store(&g_cs0[(ct * 18 + rb) * 216], s_red, 864);
                if (krot == 7) bulk_store(&g_cs0[(ct * 18 + rb + 2) * 216], s_red + 896, 864);
                bulk_commit();
                bulk_wait_all();
                flag_add(&g_cnt_a[16 + ct]);
                TL(0, 7);
                flag_wait(&g_cnt_a[16 + ct], 16);
            }
            if (blockIdx.x == 0) for (int i = lane; i < N_FLAG_C; i += 32) g_flag_c[i] = 0;
            __syncwarp();
#pragma unroll 1
            for (int c = lane; c < 54; c += 32) {
                float4 v[18];
#pragma unroll
                for (int i = 0; i < 18; i++) v[i] = __ldcg((const float4*)&g_cs0[(ct * 18 + i) * 216] + c);
#pragma unroll
                for (int i = 1; i < 18; i++) { v[0].x += v[i].x; v[0].y += v[i].y; v[0].z += v[i].z; v[0].w += v[i].w; }
                sts128(s_cs + 32 * (ct & 1) + c * 16, __float_as_uint(v[0].x), __float_as_uint(v[0].y), __float_as_uint(v[0].z), __float_as_uint(v[0].w));
            }
        } else {
            if (warp == 10) {
                if (krot == 7) stage_colsum(sb + (2 + rank) * A_STAGE_BYTES, bar_full + 16 + 8 * rank, bar_cdone, s_red + 896, ct & 1, lane);
                else if (lane == 0) mbar_arrive(bar_cdone);
                fence_async_smem();
                nbar_arrive(7, 64);
            }
            const int row = tid - 320, rl = row >> 2;
            mbar_wait_trap(bar_a, 0);
            const uint4* px = (const uint4*)(x + (size_t)(rb * 128 + ct * 16 + rl) * DM) + (lane & 3);
            uint4 v[18];
#pragma unroll
            for (int i = 0; i < 18; i++) v[i] = __ldg(px + 4 * i);
            float sum = 0.f, sq = 0.f;
#pragma unroll
            for (int i = 0; i < 18; i++) {
                sum += bf_lo(v[i].x); sum += bf_hi(v[i].x); sum += bf_lo(v[i].y); sum += bf_hi(v[i].y);
                sum += bf_lo(v[i].z); sum += bf_hi(v[i].z); sum += bf_lo(v[i].w); sum += bf_hi(v[i].w);
            }
            sum += __shfl_xor_sync(~0u, sum, 1); sum += __shfl_xor_sync(~0u, sum, 2);
            const float mean = sum * (1.f / DM);
#pragma unroll
            for (int i = 0; i < 18; i++) {
                const uint32_t w[4] = {v[i].x, v[i].y, v[i].z, v[i].w};
#pragma unroll
                for (int k = 0; k < 4; k++) { const float a = bf_lo(w[k]) - mean, b = bf_hi(w[k]) - mean; sq = fmaf(a, a, sq); sq = fmaf(b, b, sq); }
            }
            sq += __shfl_xor_sync(~0u, sq, 1); sq += __shfl_xor_sync(~0u, sq, 2);
            if ((lane & 3) == 0) sts64f(s_red + 1792 + rl * 8, mean, 1.f / sqrtf(sq * (1.f / DM) + LN_EPS));
            fence_async_smem();
            nbar_sync(1, 64);
            if (row == 0) {
                bulk_store(&g_xstat[rb * 128 + ct * 16], s_red + 1792, 128);
                bulk_commit();
                bulk_wait_all();
                flag_add(&g_cnt_a[rb]);
                TL(0, 8);
                flag_wait(&g_cnt_a[rb], 8);
                mbar_expect(bar_st, 1024);
                bulk_load(s_st, &g_xstat[rb * 128], 1024, bar_st);
                mbar_wait_trap(bar_st, 0);
                TL(0, 6);
            }
            __syncwarp();
            mbar_wait_trap(bar_dead, 0);
            const uint32_t sel0 = ((POLY_PATTERN >> (row >> 3)) & 1) ? 0x3F803F80u : 0u, sel1 = ((POLY_PATTERN >> ((row >> 3) + 8)) & 1) ? 0x3F803F80u : 0u;
#pragma unroll 1
            for (int p = 0; p < 3; p++) {
                const int kind = (ct * 3 + p) >> 3;
                const uint32_t gs = kind == 2 ? 384u : 128u;
                const uint32_t a = sb + A_OFF_STG + p * 4 * BLK_BYTES + (row & 7) * 16 + (row >> 3) * gs + (kind == 2 ? 256u : 4096u);
                const uint32_t w0 = kind == 0 ? 0x42FE47C0u : kind == 2 ? 0x00003F80u : sel0, w1 = kind == 1 ? sel1 : w0;
#pragma unroll
                for (int i = 0; i < 4; i++) {
                    sts32(a + i * BLK_BYTES + 4, w0); sts64f(a + i * BLK_BYTES + 8, 0.f, 0.f);
                    sts32(a + i * BLK_BYTES + 8 * gs + 4, w1); sts64f(a + i * BLK_BYTES + 8 * gs + 8, 0.f, 0.f);
                }
            }
            fence_async_smem();
        }
        __syncwarp();
        nbar_arrive(2, 352);
    } else {
        const int wg = warp >> 2;
        float acc[112];
#pragma unroll
        for (int i = 0; i < 112; i++) acc[i] = 0.f;
        const uint32_t a_lo = desc_addr(sb + wg * 8192) | (1u << 16);
        const uint32_t b_lo = desc_addr(sb) | ((1024 >> 4) << 16);
        const uint32_t rel = (tid & 127) == 0 ? bar_empty : mapa(bar_empty, rank ^ 1);
        const bool do_rel = (tid & 95) == 0;
#pragma unroll 1
        for (int s = 0; s < 18; s++) {
            const int slot = s >= A_STAGES ? s - A_STAGES : s;
            if (!(s & 1)) mbar_wait(bar_a + 4 * s, 0);
            if (tid == 0) TC(0, 64 + s);
            mbar_wait(bar_full + 8 * slot, s >= A_STAGES);
            if (tid == 0 && s == 0) TL(0, 1);
            if (tid == 0) TC(0, 1 + s);
            const uint32_t al = a_lo + (x_slot(s >> 1) >> 4) + (s & 1) * 4, bl = b_lo + slot * (A_STAGE_BYTES >> 4);
            wg_fence();
            mma_ss_n224(acc, al, HI_SW128, bl, HI_SW64, 1);
            mma_ss_n224(acc, al + 2, HI_SW128, bl + (7168 >> 4), HI_SW64, 1);
            wg_commit();
            wg_wait<1>();
            if (s == 1) mbar_wait(bar_cdone, 0);
            if (do_rel && s >= 1 && s <= 18 - A_STAGES) mbar_arrive_cluster(rel + 8 * (s - 1));
            if ((tid & 127) == 64) {
                if (s >= 2 && s <= 10 && !(s & 1)) mbar_arrive(bar_xfree + 4 * (s - 2));
                if (s == 12) mbar_arrive(bar_dead);
            }
        }
        wg_wait<0>();
        fence_regs(acc);
        if (tid == 0) { TL(0, 2); TC(0, 20); }
        nbar_sync(2, 352);
        if (tid == 0) { TL(0, 3); TC(0, 21); }
        const float2 st0 = lds64f(s_st + (warp * 16 + (lane >> 2)) * 8), st1 = lds64f(s_st + (warp * 16 + 8 + (lane >> 2)) * 8);
        if (ct & 1) qkv_epilogue<1>(acc, sb + A_OFF_STG, s_cs, bar_out, st0, st1, ct, rb, warp, lane);
        else qkv_epilogue<0>(acc, sb + A_OFF_STG, s_cs, bar_out, st0, st1, ct, rb, warp, lane);
    }
}

constexpr uint32_t B_OFF_Q = 2 * SLOT_BYTES, B_OFF_KMAX = B_OFF_Q + 4 * BLK_BYTES, B_OFF_BAR = B_OFF_KMAX + 1024;
constexpr uint32_t B_SMEM = B_OFF_BAR + 64;
constexpr uint32_t QK_LBO = (2048 >> 4) << 16, V_LBO = (384 >> 4) << 16, HI_NOSW = 128 >> 4;

__device__ __forceinline__ uint32_t exp_pair_poly(float a, float b, uint32_t c_or, uint32_t c_mul) {
    const uint32_t u = __byte_perm(__float_as_uint(a), __float_as_uint(b), 0x5410);
    uint32_t g, w, p, r;
    asm("lop3.b32 %0, %1, 0x007F007F, %2, 0xEA;" : "=r"(g) : "r"(u), "r"(c_or));
    asm("fma.rn.f16x2 %0, %1, %2, %3;" : "=r"(w) : "r"(g), "r"(c_mul), "r"(0xC40EC40Eu));
    asm("fma.rn.f16x2 %0, %1, %1, %2;" : "=r"(p) : "r"(w), "r"(0x47AE47AEu));
    asm("lop3.b32 %0, %1, %2, 0x007F007F, 0xD8;" : "=r"(r) : "r"(u), "r"(p));
    return r;
}
template <int JOFF>
__device__ __forceinline__ void exp_tile(const float (&s)[32], uint32_t (&p)[16], uint32_t c_or, uint32_t c_mul) {
#pragma unroll
    for (int j = 0; j < 8; j++) {
        if ((POLY_PATTERN >> (j + JOFF)) & 1) {
            p[2 * j] = exp_pair_poly(s[4 * j], s[4 * j + 1], c_or, c_mul);
            p[2 * j + 1] = exp_pair_poly(s[4 * j + 2], s[4 * j + 3], c_or, c_mul);
        } else {
            p[2 * j] = pack_bf16(ex2(s[4 * j]), ex2(s[4 * j + 1]));
            p[2 * j + 1] = pack_bf16(ex2(s[4 * j + 2]), ex2(s[4 * j + 3]));
        }
    }
}
__device__ __forceinline__ void qk_tile(float (&s)[32], const uint32_t (&q)[8], uint64_t k) {
    mma_qk_first(s, q[0], q[1], q[2], q[3], k + QK_LBO);
    mma_qk_second(s, q[4], q[5], q[6], q[7], k + 256);
}
__device__ __forceinline__ void pv_tile(float (&o)[12], const uint32_t (&p)[16], uint64_t v) {
#pragma unroll
    for (int kk = 0; kk < 4; kk++) mma_pv(o, p[4 * kk], p[4 * kk + 1], p[4 * kk + 2], p[4 * kk + 3], v + kk * 48);
}
__device__ __forceinline__ void load_q(uint32_t (&q)[8], uint32_t sq) {
    q[0] = lds32(sq); q[1] = lds32(sq + 128); q[2] = lds32(sq + 2048); q[3] = lds32(sq + 2176);
    q[4] = lds32(sq + 4096); q[5] = lds32(sq + 4224); q[6] = lds32((sq + 4096) | 12); q[7] = lds32((sq + 4224) | 12);
}
__device__ __forceinline__ float q_l1(const uint32_t (&q)[8], int lane) {
    const bool first = (lane & 3) == 0;
    float n0 = fabsf(bf_lo(q[0])) + fabsf(bf_hi(q[0])) + fabsf(bf_lo(q[2])) + fabsf(bf_hi(q[2])) + (first ? fabsf(bf_lo(q[4])) + fabsf(bf_hi(q[4])) : 0.f);
    float n1 = fabsf(bf_lo(q[1])) + fabsf(bf_hi(q[1])) + fabsf(bf_lo(q[3])) + fabsf(bf_hi(q[3])) + (first ? fabsf(bf_lo(q[5])) + fabsf(bf_hi(q[5])) : 0.f);
    n0 += __shfl_xor_sync(~0u, n0, 1); n1 += __shfl_xor_sync(~0u, n1, 1);
    n0 += __shfl_xor_sync(~0u, n0, 2); n1 += __shfl_xor_sync(~0u, n1, 2);
    return n0 > n1 || n0 != n0 ? n0 : n1;
}
__device__ __forceinline__ void store_attn(const float (&o)[12], __nv_bfloat16* row, int h, int lane) {
    const float r0 = __fdividef(1.f, __shfl_sync(~0u, o[8], (lane & ~3) | 1)), r1 = __fdividef(1.f, __shfl_sync(~0u, o[10], (lane & ~3) | 1));
    *(uint2*)(row + h * 16 + (lane & 3) * 4) = make_uint2(pack_bf16(o[0] * r0, o[1] * r0), pack_bf16(o[4] * r0, o[5] * r0));
    *(uint2*)(row + 8 * DM + h * 16 + (lane & 3) * 4) = make_uint2(pack_bf16(o[2] * r1, o[3] * r1), pack_bf16(o[6] * r1, o[7] * r1));
    if ((lane & 3) == 0) {
        *(uint32_t*)(row + 512 + h * 2) = pack_bf16(o[8] * r0, o[9] * r0);
        *(uint32_t*)(row + 8 * DM + 512 + h * 2) = pack_bf16(o[10] * r1, o[11] * r1);
    }
}
__device__ __forceinline__ bool wg_any(bool pred, uint32_t id) {
    uint32_t r;
    asm volatile("{\n.reg .pred p, q;\nsetp.ne.u32 p, %1, 0;\nbar.red.or.pred q, %2, 128, p;\nselp.u32 %0, 1, 0, q;\n}\n" : "=r"(r) : "r"((uint32_t)pred), "r"(id) : "memory");
    return __any_sync(~0u, r);
}
__device__ __forceinline__ void attn_safe_block(uint64_t k0, uint32_t (&q)[8], float (&o)[12]) {
    if (threadIdx.x & 3) { q[4] = 0; q[5] = 0; }
    float s[32], m0 = -INFINITY, m1 = -INFINITY;
    uint32_t p[16];
#pragma unroll
    for (int i = 0; i < 12; i++) o[i] = 0.f;
#pragma unroll 1
    for (int i = 0; i < 32; i++) {
        wg_fence();
        qk_tile(s, q, k0 + (i >> 1) * 384 + (i & 1) * 64);
        wg_commit();
        wg_wait<0>();
        fence_regs(s);
        float n0 = m0, n1 = m1;
#pragma unroll
        for (int j = 0; j < 8; j++) { n0 = fmaxf(n0, fmaxf(s[4 * j], s[4 * j + 1])); n1 = fmaxf(n1, fmaxf(s[4 * j + 2], s[4 * j + 3])); }
        n0 = fmaxf(n0, __shfl_xor_sync(~0u, n0, 1)); n0 = fmaxf(n0, __shfl_xor_sync(~0u, n0, 2));
        n1 = fmaxf(n1, __shfl_xor_sync(~0u, n1, 1)); n1 = fmaxf(n1, __shfl_xor_sync(~0u, n1, 2));
        const float c0 = ex2(m0 - n0), c1 = ex2(m1 - n1);
        m0 = n0; m1 = n1;
#pragma unroll
        for (int j = 0; j < 3; j++) { o[4 * j] *= c0; o[4 * j + 1] *= c0; o[4 * j + 2] *= c1; o[4 * j + 3] *= c1; }
#pragma unroll
        for (int j = 0; j < 8; j++) {
            p[2 * j] = pack_bf16(ex2(s[4 * j] - m0), ex2(s[4 * j + 1] - m0));
            p[2 * j + 1] = pack_bf16(ex2(s[4 * j + 2] - m1), ex2(s[4 * j + 3] - m1));
        }
        fence_regs(o);
        wg_fence();
        pv_tile(o, p, k0 + (SLOT_BYTES >> 4) + V_LBO + i * 192);
        wg_commit();
        wg_wait<0>();
        fence_regs(o);
    }
}

__global__ void __launch_bounds__(512, 1)
attn_kernel(const __grid_constant__ CUtensorMap tm_wo, const __grid_constant__ CUtensorMap tm_wo2, const __nv_bfloat16* __restrict__ w1, const __nv_bfloat16* __restrict__ w2) {
    extern __shared__ __align__(128) uint8_t smem_raw[];
    const int tid = threadIdx.x, lane = tid & 31;
    if (tid == 0) TL(1, 0);
    const uint32_t sk = smem_u32(smem_raw), sv = sk + SLOT_BYTES, bar = sk + B_OFF_BAR;
    if (blockIdx.x < 4) {
        pdl_launch();
        if (tid == 480) {
            mbar_init(bar, 1);
            fence_mbar_init();
            fence_async_smem();
            mbar_expect(bar, 2 * 82944);
#pragma unroll 1
            for (int i = 0; i < 4; i++)
                asm volatile("cp.async.bulk.tensor.4d.shared::cluster.global.mbarrier::complete_tx::bytes [%0], [%1, {%3, %4, %4, %5}], [%2];"
                             :: "r"(sk + 16384 + (i >> 1) * 82944 + (i & 1) * 36864), "l"(&tm_wo), "r"(bar), "r"((blockIdx.x * 2 + (i >> 1)) * 72), "r"(0), "r"((i & 1) * 16) : "memory");
#pragma unroll 1
            for (int i = 0; i < 2; i++)
                asm volatile("cp.async.bulk.tensor.5d.shared::cluster.global.mbarrier::complete_tx::bytes [%0], [%1, {%3, %4, %4, %4, %4}], [%2];"
                             :: "r"(sk + 16384 + i * 82944 + 73728), "l"(&tm_wo2), "r"(bar), "r"((blockIdx.x * 2 + i) * 72), "r"(0) : "memory");
            mbar_wait(bar, 0);
            bulk_store(g_wo_img + blockIdx.x * 2 * 82944, sk + 16384, 2 * 82944);
            bulk_commit();
            bulk_wait_all();
#pragma unroll 1
            for (int i = 0; i < 32; i++) l2_prefetch((const uint8_t*)w2 + (size_t)(blockIdx.x * 32 + i) * 41472, 41472);
            pdl_wait();
            flag_add(&g_flag_c[FLAG_WO + blockIdx.x * 2]);
            flag_add(&g_flag_c[FLAG_WO + blockIdx.x * 2 + 1]);
        }
        float* red = (float*)smem_raw;
        const int cg = tid % 144, part = tid / 144;
        float c[8] = {0.f, 0.f, 0.f, 0.f, 0.f, 0.f, 0.f, 0.f};
        if (part < 3) {
            const uint4* pw = (const uint4*)(w1 + (size_t)part * 192 * FF + blockIdx.x * 1152) + cg;
#pragma unroll 16
            for (int k = 0; k < 192; k++) {
                const uint4 v = __ldg(pw + (size_t)k * (FF / 8));
                c[0] += bf_lo(v.x); c[1] += bf_hi(v.x); c[2] += bf_lo(v.y); c[3] += bf_hi(v.y);
                c[4] += bf_lo(v.z); c[5] += bf_hi(v.z); c[6] += bf_lo(v.w); c[7] += bf_hi(v.w);
            }
#pragma unroll
            for (int k = 0; k < 8; k++) red[part * 1152 + cg * 8 + k] = c[k];
        }
        __syncthreads();
        for (int i = tid; i < 144 * 8; i += 512) {
            const int core = i >> 3, k = i & 7;
            uint32_t w[4] = {0u, 0u, 0u, 0u};
            if (k < 3) {
#pragma unroll
                for (int j = 0; j < 4; j++) {
                    const int c0 = core * 8 + 2 * j;
                    const float a = -(red[c0] + red[1152 + c0] + red[2304 + c0]), b = -(red[c0 + 1] + red[1153 + c0] + red[2305 + c0]);
                    const uint32_t hi = pack_bf16(a, b);
                    w[j] = k == 1 ? pack_bf16(a - bf_lo(hi), b - bf_hi(hi)) : hi;
                }
            }
            ((uint4*)g_cs1)[blockIdx.x * 1152 + i] = make_uint4(w[0], w[1], w[2], w[3]);
        }
        if (tid == 0) TL(1, 5);
        return;
    }
    const int h = (blockIdx.x - 4) >> 2, qt = blockIdx.x & 3;
    if (lane == 0 && tid < 96) {
        mbar_init(bar + (tid >> 2), 1);
        fence_mbar_init();
    }
    if (tid == 160) { sts32(bar + 40, 0x48004800u); sts32(bar + 44, 0x38A038A0u); }
    __syncthreads();
    const uint32_t c_or = lds32(bar + 40), c_mul = lds32(bar + 44);
    {
        const int w = tid >> 7;
        const uint8_t* src = g_qkv + (size_t)((w & 1) * (16 + 16 * w) + h) * SLOT_BYTES + ((w & 1) ? 0 : (qt * 4 + w) * BLK_BYTES);
        const uint32_t dst = (w & 1) ? sk + (w >> 1) * SLOT_BYTES : sk + B_OFF_Q + w * BLK_BYTES;
        uint32_t bytes = (w & 1) ? BLK_BYTES : 2 * BLK_BYTES;
        if (tid == 0) mbar_expect(bar, 6 * BLK_BYTES);
        asm volatile("" : "+l"(src), "+r"(bytes) :: "memory");
        pdl_wait();
        if ((tid & 127) == 0) bulk_load(dst, src, bytes, bar);
        pdl_launch();
    }
    if (tid == 0) { TL(1, 1); TC(1, 0);
    }
    const uint8_t* gk = g_qkv + (size_t)(32 + h) * SLOT_BYTES;
    auto load_kv = [&](uint32_t off, uint32_t bytes, uint32_t b) {
        bulk_load(sk + off, gk + off, bytes, b);
        bulk_load(sv + off, gk + 32 * SLOT_BYTES + off, bytes, b);
    };
    const uint64_t k0 = desc_addr(sk) | ((uint64_t)HI_NOSW << 32);
    const uint32_t sq = sk + B_OFF_Q + (tid >> 8) * BLK_BYTES + ((tid >> 5) & 7) * 256 + lane * 4;
    float oa[12], ob[12];
#pragma unroll
    for (int i = 0; i < 12; i++) { oa[i] = 0.f; ob[i] = 0.f; }
    mbar_wait(bar, 0);
    uint32_t qa[8], qb[8];
    load_q(qa, sq);
    load_q(qb, sq + 2 * BLK_BYTES);
    fence_regs(oa); fence_regs(ob); fence_regs(qa); fence_regs(qb);
    {
        float s[32]; uint32_t p[16];
        uint64_t k = k0;
#pragma unroll 1
        for (int seg = 0; seg < 3; seg++) {
            mbar_wait(bar + 8 * seg, 0);
            if (seg == 0 && tid == 256) { mbar_expect(bar + 8, 6 * BLK_BYTES); load_kv(BLK_BYTES, 3 * BLK_BYTES, bar + 8); }
            if (seg == 1 && tid == 384) {
                mbar_expect(bar + 16, 24 * BLK_BYTES + 1024);
                load_kv(4 * BLK_BYTES, 12 * BLK_BYTES, bar + 16);
                bulk_load(sk + B_OFF_KMAX, g_kmax + ((32 + h) / 12) * 128, 512, bar + 16);
                bulk_load(sk + B_OFF_KMAX + 512, g_kmax + ((64 + h) / 12) * 128, 512, bar + 16);
            }
            __syncwarp();
            if (tid == 0 && seg == 0) TL(1, 2);
            if ((tid & 127) == 0) TC(1, 16 + (tid >> 7) * 16 + seg);
            const int nblk = seg == 0 ? 1 : seg == 1 ? 3 : 12;
#pragma unroll 1
            for (int b = 0; b < nblk; b++, k += 384) {
                const uint64_t v = k + (SLOT_BYTES >> 4) + V_LBO;
                wg_fence();
                qk_tile(s, qa, k);
                wg_commit();
                wg_wait<0>();
                fence_regs(s); fence_regs(p);
                exp_tile<0>(s, p, c_or, c_mul);
                wg_fence();
                pv_tile(oa, p, v);
                qk_tile(s, qb, k);
                wg_commit();
                wg_wait<0>();
                fence_regs(s); fence_regs(p);
                exp_tile<0>(s, p, c_or, c_mul);
                wg_fence();
                pv_tile(ob, p, v);
                qk_tile(s, qa, k + 64);
                wg_commit();
                wg_wait<0>();
                fence_regs(s); fence_regs(p);
                exp_tile<8>(s, p, c_or, c_mul);
                wg_fence();
                pv_tile(oa, p, v + 192);
                qk_tile(s, qb, k + 64);
                wg_commit();
                wg_wait<0>();
                fence_regs(s); fence_regs(p);
                exp_tile<8>(s, p, c_or, c_mul);
                wg_fence();
                pv_tile(ob, p, v + 192);
                wg_commit();
            }
        }
    }
    if ((tid & 127) == 0) TC(1, 16 + (tid >> 7) * 16 + 5);
    const uint4 km = lds128(sk + B_OFF_KMAX + lane * 16), vm = lds128(sk + B_OFF_KMAX + 512 + lane * 16);
    const float kmax = __uint_as_float(__reduce_max_sync(~0u, max(max(km.x, km.y), max(km.z, km.w))));
    const float vmax = __uint_as_float(__reduce_max_sync(~0u, max(max(vm.x, vm.y), max(vm.z, vm.w))));
    const bool unsafe = wg_any(!(fmaxf(q_l1(qa, lane), q_l1(qb, lane)) * kmax <= 100.f && vmax <= 32768.f), 1 + (tid >> 7));
    if ((tid & 127) == 0) TC(1, 16 + (tid >> 7) * 16 + 6);
    wg_wait<0>();
    fence_regs(oa); fence_regs(ob);
    if ((tid & 127) == 0) TC(1, 16 + (tid >> 7) * 16 + 7);
    __nv_bfloat16* po = g_attn + (size_t)(qt * 512 + (tid >> 5) * 16 + (lane >> 2)) * DM;
    if (!unsafe) {
        store_attn(oa, po, h, lane);
        if ((tid & 127) == 0) TC(1, 16 + (tid >> 7) * 16 + 8);
        store_attn(ob, po + 256 * DM, h, lane);
    } else {
#pragma unroll 1
        for (int u = 0; u < 2; u++) {
            load_q(qa, sq + u * 2 * BLK_BYTES);
            attn_safe_block(k0, qa, oa);
            store_attn(oa, po + u * 256 * DM, h, lane);
        }
    }
    if ((tid & 127) == 0) { TL(1, 5 + (tid >> 7)); TC(1, 1 + (tid >> 7)); }
}

constexpr uint32_t C_HALF = 73728;
constexpr uint32_t C_OFF_W = 147456, C_SLOT = 6144;
constexpr uint32_t C_OFF_CS = C_OFF_W + 12 * C_SLOT;
constexpr uint32_t C_OFF_BAR = C_OFF_W + 82944;
constexpr uint32_t C_OFF_HST = C_OFF_BAR + 512;
constexpr uint32_t C_SMEM = C_OFF_HST + 1024 + 512;

struct RowStat { float mean, rstd; };
__device__ __forceinline__ RowStat combine_hstat(float2 u, float2 v) {
    float sum = u.x + v.x;
    sum += __shfl_xor_sync(~0u, sum, 1); sum += __shfl_xor_sync(~0u, sum, 2);
    const float mean = sum * (1.f / DM);
    const float d0 = u.x * (1.f / 72) - mean, d1 = v.x * (1.f / 72) - mean;
    float m2 = u.y + v.y + 72.f * (d0 * d0 + d1 * d1);
    m2 += __shfl_xor_sync(~0u, m2, 1); m2 += __shfl_xor_sync(~0u, m2, 2);
    return {mean, 1.f / sqrtf(m2 * (1.f / DM) + LN_EPS)};
}
__device__ __forceinline__ uint32_t mean_frag(float m, int t) {
    const uint32_t hi = pack_bf16(m, m);
    return t == 0 ? hi : t == 1 ? pack_bf16(m - bf_lo(hi), 0.f) : 0u;
}
__device__ __forceinline__ void add_partial(float (&acc)[32], uint32_t src) {
#pragma unroll
    for (int i = 0; i < 4; i++) {
        const uint4 v = lds128(src + i * 512);
        acc[8 * i] += bf_lo(v.x); acc[8 * i + 1] += bf_hi(v.x); acc[8 * i + 2] += bf_lo(v.y); acc[8 * i + 3] += bf_hi(v.y);
        acc[8 * i + 4] += bf_lo(v.z); acc[8 * i + 5] += bf_hi(v.z); acc[8 * i + 6] += bf_lo(v.w); acc[8 * i + 7] += bf_hi(v.w);
    }
}

__global__ void __launch_bounds__(384, 1)
ffn_kernel(const __grid_constant__ CUtensorMap tm_attn, const __grid_constant__ CUtensorMap tm_w1, const __grid_constant__ CUtensorMap tm_w2,
           const __grid_constant__ CUtensorMap tm_out, const __nv_bfloat16* __restrict__ x, __nv_bfloat16* __restrict__ out) {
    extern __shared__ uint8_t smem_raw[];
    const int tid = threadIdx.x, warp = __shfl_sync(~0u, tid >> 5, 0), lane = tid & 31;
    const uint32_t sb = (smem_u32(smem_raw) + 1023u) & ~1023u;
    const uint32_t bar_a = sb + C_OFF_BAR, bar_full = bar_a + 72, bar_wo = bar_full + 96, bar_cs = bar_wo + 8, bar_recv = bar_cs + 8;
    const uint32_t bar_sfree = bar_recv + 16, bar_hst = bar_sfree + 16, bar_h = bar_hst + 8, bar_g1 = bar_h + 64, bar_hrd = bar_g1 + 8;
    const uint32_t bar_sdone = bar_hrd + 8, bar_empty = bar_sdone + 8, bar_pub = bar_empty + 96;
    const int rb = blockIdx.x & 15, e = blockIdx.x >> 4;
    const uint32_t rank = blockIdx.x & 1;
    const int wrb = blockIdx.x >> 3, wsl = blockIdx.x & 7;
    if (tid == 0) { TL(2, 0); TC(2, 0); }

    if (lane == 0) {
        uint32_t wo_ready = 0;
        if (warp == 9) asm volatile("ld.relaxed.gpu.global.u32 %0, [%1];" : "=r"(wo_ready) : "l"(&g_flag_c[FLAG_WO + wsl]) : "memory");
#pragma unroll
        for (int i = 0; i < 5; i++) {
            const int b = warp + 12 * i;
            if (b < 53) mbar_init(bar_a + 8 * b, b < 28 ? 1 : b < 39 ? 2 : 4);
        }
        fence_mbar_init();
        mbar_expect(bar_a + 8 * (warp < 9 ? warp + 12 : warp), C_SLOT);
        if (warp == 9) {
            if (!wo_ready) flag_wait_soft(&g_flag_c[FLAG_WO + wsl], 1);
            mbar_expect(bar_wo, 82944);
#pragma unroll 1
            for (int i = 0; i < 3; i++) bulk_load(sb + C_OFF_W + i * 27648, g_wo_img + wsl * 82944 + i * 27648, 27648, bar_wo);
        }
    }
    __syncwarp();
    if (tid == 320) { tma_prefetch_desc(&tm_attn); tma_prefetch_desc(&tm_w1); tma_prefetch_desc(&tm_w2); tma_prefetch_desc(&tm_out); }
    cluster_sync();

    if (warp >= 8) {
        asm volatile("setmaxnreg.dec.sync.aligned.u32 24;");
        if (warp == 8) {
            if (lane == 0) {
                if (blockIdx.x == 0) for (int i = 0; i < 24; i++) g_cnt_a[i] = 0;
                pdl_wait();
                TL(2, 1); TC(2, 1);
#pragma unroll 1
                for (int kc = 0; kc < 9; kc++) {
                    mbar_expect(bar_a + 8 * kc, 16384);
                    if (kc < NOMC) {
                        tma_2d(sb + kc * 16384, &tm_attn, kc * 64, wrb * 128, bar_a + 8 * kc);
                        tma_2d(sb + kc * 16384 + 8192, &tm_attn, kc * 64, wrb * 128 + 64, bar_a + 8 * kc);
                    } else
                    tma_2d_mc(sb + kc * 16384 + rank * 8192, &tm_attn, kc * 64, wrb * 128 + rank * 64, bar_a + 8 * kc);
                    if (kc == 0) TC(2, 8);
                    if (kc == 8) TC(2, 14);
                }
                uint32_t ph = 0;
#pragma unroll 1
                for (int rnd = 0; rnd < 18; rnd++) {
                    const int pass = rnd / 3, p = rnd - 9;
                    const int c0 = rnd < 9 ? e * 576 + pass * 192 : (p == 0 ? 8 : (e + p) & 7) * 64;
                    const int r0 = rnd < 9 ? (rnd - pass * 3) * 192 : e * 576;
#pragma unroll 1
                    for (int slot = rank; slot < 12; slot += 2) {
                        mbar_wait_trap(bar_empty + 8 * slot, ph);
                        TC(2, 128 + rnd * 6 + (slot >> 1));
                        if (rnd < 9) tma_3d_mc(sb + C_OFF_W + slot * C_SLOT, &tm_w1, c0, r0 + slot * 16, bar_full + 8 * slot);
                        else tma_2d_mc(sb + C_OFF_W + slot * C_SLOT, &tm_w2, c0, r0 + slot * 48, bar_full + 8 * slot);
                    }
                    ph ^= 1;
                }
            }
        } else if (warp == 11) {
            mbar_wait_trap(bar_hrd, 0);
            if (lane == 0) {
                mbar_expect(bar_cs, 9216);
                bulk_load(sb + C_OFF_CS, g_cs1 + e * 9216, 9216, bar_cs);
                flag_wait(&g_flag_c[FLAG_HST + rb], 16);
                mbar_arrive(bar_hst);
            }
            __syncwarp();
            mbar_wait_trap(bar_g1, 0, LONG_NS);
            const int r = lane >> 2, t = lane & 3, row = rb * 128 + e * 16 + r;
            const float rs0 = combine_hstat(__ldcg(&g_hstat[2 * t * SEQ + row]), __ldcg(&g_hstat[(2 * t + 1) * SEQ + row])).rstd;
            const float rs1 = combine_hstat(__ldcg(&g_hstat[2 * t * SEQ + row + 8]), __ldcg(&g_hstat[(2 * t + 1) * SEQ + row + 8])).rstd;
            const uint32_t tmp = sb + ((e + 2) & 7) * 8192;
            if (lane < 8) flag_wait(&g_flag_c[FLAG_PART + (rb * 9 + 8) * 8 + lane], 2);
            __syncwarp();
            if (lane == 0) {
                mbar_expect(bar_cs, 16384);
#pragma unroll 1
                for (int c = 0; c < 8; c++)
                    bulk_load(tmp + (c >> 2) * C_HALF + (c & 3) * 2048, g_part + (size_t)((rb * 9 + 8) * 8 + c) * 16384 + e * 2048, 2048, bar_cs);
            }
            mbar_wait_trap(bar_cs, 1);
#pragma unroll 1
            for (int i = 0; i < 8; i++) {
                const uint32_t* ph = (const uint32_t*)(g_h + rb * 147456 + (e >> 2) * C_HALF + (64 + i) * 1024 + (e & 3) * 256) + lane;
                const uint32_t h0 = __ldcg(ph), h1 = __ldcg(ph + 32);
                float a0 = 0.f, a1 = 0.f, a2 = 0.f, a3 = 0.f;
#pragma unroll
                for (int c = 0; c < 8; c++) {
                    const float2 v = lds64f(tmp + (c >> 2) * C_HALF + (c & 3) * 2048 + (i >> 1) * 512 + lane * 16 + (i & 1) * 8);
                    a0 += bf_lo(__float_as_uint(v.x)); a1 += bf_hi(__float_as_uint(v.x)); a2 += bf_lo(__float_as_uint(v.y)); a3 += bf_hi(__float_as_uint(v.y));
                }
                uint32_t* po = (uint32_t*)out + ((size_t)row * DM + 512 + 8 * i) / 2 + t;
                po[0] = pack_bf16(bf_lo(h0) + rs0 * a0, bf_hi(h0) + rs0 * a1);
                po[4 * DM] = pack_bf16(bf_lo(h1) + rs1 * a2, bf_hi(h1) + rs1 * a3);
            }
            fence_async_smem();
            __syncwarp();
            if (lane == 0) { mbar_expect(bar_recv, 6 * 16384); mbar_expect(bar_recv + 8, 16384); }
#pragma unroll 1
            for (uint32_t p = 1, it = 0; p < 8; it++) {
                const uint32_t m = flag_poll(&g_flag_c[FLAG_PART + (rb * 9 + e) * 8 + ((e - lane) & 7)], lane < 8, 2);
#pragma unroll 1
                for (; p < 8 && ((m >> p) & 1); p++) {
                    if (lane == 0) {
                        const int c = (e - p) & 7;
                        const uint8_t* src = g_part + (size_t)((rb * 9 + e) * 8 + c) * 16384;
                        if (p == 7) mbar_wait_trap(bar_sdone, 0);
                        const uint32_t dst = sb + (p == 7 ? 8 : c) * 8192;
                        bulk_load(dst, src, 8192, bar_recv + (p == 7 ? 8 : 0));
                        bulk_load(dst + C_HALF, src + 8192, 8192, bar_recv + (p == 7 ? 8 : 0));
                    }
                    __syncwarp();
                }
                if (POLL_SLEEP && p < 6) __nanosleep(POLL_SLEEP);
                if (it > SPIN_LIMIT) __trap();
            }
        } else {
            const int w = warp - 9;
            if (lane == 0) {
                mbar_wait_trap(bar_pub + 8 * w, 0);
                fence_async_smem();
                bulk_store(g_h + wrb * 147456 + w * C_HALF + wsl * 9216, sb + w * 9216, 9216);
                bulk_commit();
                bulk_wait_all();
                flag_add(&g_flag_c[FLAG_H + (wrb * 2 + w) * 8 + wsl]);
                mbar_arrive(bar_hrd);
                if (w == 0) TC(2, 4);
            }
            __syncwarp();
            mbar_wait_trap(bar_hrd, 0);
#pragma unroll 1
            for (uint32_t sl = 0, it = 0; sl < 8; it++) {
                const uint32_t m = flag_poll(&g_flag_c[FLAG_H + (rb * 2 + w) * 8 + (lane & 7)], lane < 8, 1);
#pragma unroll 1
                for (; sl < 8 && ((m >> sl) & 1); sl++) {
                    if (lane == 0) {
                        if (sl == 0 && w == 0) TC(2, 5);
                        if (HPACE && sl >= HPACE) mbar_wait_trap(bar_h + 8 * (sl - HPACE), 0);
                        mbar_expect(bar_h + 8 * sl, 9216);
                        bulk_load(sb + w * C_HALF + sl * 9216, g_h + rb * 147456 + w * C_HALF + sl * 9216, 9216, bar_h + 8 * sl);
                    }
                    __syncwarp();
                }
                if (it > SPIN_LIMIT) __trap();
            }
            if (lane == 0) {
                if (w == 0) { TL(2, 4); TC(2, 7); }
                mbar_wait_trap(bar_pub + 8 * w, 1);
                fence_async_smem();
                bulk_store(&g_hstat[wsl * SEQ + wrb * 128 + w * 64], sb + C_OFF_HST + w * 512, 512);
                bulk_commit();
                bulk_wait_all();
                flag_add(&g_flag_c[FLAG_HST + wrb]);
#pragma unroll 1
                for (int p = 0; p < 8; p++) {
                    const int idx = (rb * 9 + (p == 0 ? 8 : (e + p) & 7)) * 8 + e;
                    mbar_wait_trap(bar_pub + 8 * w, p & 1, LONG_NS);
                    fence_async_smem();
                    bulk_store(g_part + (size_t)idx * 16384 + w * 8192, sb + w * C_HALF + 65536, 8192);
                    bulk_commit();
                    bulk_wait_all();
                    flag_add(&g_flag_c[FLAG_PART + idx]);
                    mbar_arrive(bar_sfree + 8 * w);
                }
                mbar_arrive(bar_sdone);
            }
        }
    } else {
        asm volatile("setmaxnreg.inc.sync.aligned.u32 240;");
        const int wg = warp >> 2, t = lane & 3, r = lane >> 2;
        const uint32_t rel = mapa(bar_empty, warp & 1);
        const bool rel_even = (tid & 127) == 0, rel_odd = (tid & 127) == 32, arm = tid == 64;
        {
            const uint32_t* px = (const uint32_t*)(x + (size_t)(wrb * 128 + warp * 16 + r) * DM + wsl * 72) + t;
            uint32_t xr[18];
#pragma unroll
            for (int j = 0; j < 9; j++) { xr[2 * j] = __ldg(px + 4 * j); xr[2 * j + 1] = __ldg(px + 8 * (DM / 2) + 4 * j); }
            float acc[36];
#pragma unroll
            for (int i = 0; i < 36; i++) acc[i] = 0.f;
            fence_regs(acc);
            const uint32_t a_lo = desc_addr(sb + wg * 8192) | (1u << 16);
            const uint32_t b_lo = desc_addr(sb + C_OFF_W) | ((128 >> 4) << 16);
            mbar_wait(bar_wo, 0);
            if (tid == 0) TC(2, 6);
#pragma unroll 1
            for (int kc = 0; kc < 9; kc++) {
                mbar_wait(bar_a + 8 * kc, 0);
                if (tid == 0) TC(2, 240 + kc);
                wg_fence();
#pragma unroll
                for (int j = 0; j < 4; j++) mma_ss_n72(acc, a_lo + kc * 1024 + j * 2, HI_SW128, b_lo + (kc * 4 + j) * 144, 256 >> 4, 1);
                wg_commit();
            }
            wg_wait<0>();
            fence_regs(acc);
            if (tid == 0) { TL(2, 2); TC(2, 2); }
            if (rel_even || rel_odd) {
#pragma unroll
                for (int i = 0; i < 6; i++) mbar_arrive_cluster(rel + 8 * (warp & 1) + 16 * i);
            }
            uint32_t hw[18];
#pragma unroll
            for (int j = 0; j < 9; j++) {
                hw[2 * j] = pack_bf16(acc[4 * j] + bf_lo(xr[2 * j]), acc[4 * j + 1] + bf_hi(xr[2 * j]));
                hw[2 * j + 1] = pack_bf16(acc[4 * j + 2] + bf_lo(xr[2 * j + 1]), acc[4 * j + 3] + bf_hi(xr[2 * j + 1]));
            }
            nbar_sync(1, 256);
            const uint32_t hs = sb + wg * 9216 + (warp & 3) * 256 + lane * 4;
#pragma unroll
            for (int j = 0; j < 9; j++) { sts32(hs + 1024 * j, hw[2 * j]); sts32(hs + 1024 * j + 128, hw[2 * j + 1]); }
            __syncwarp();
            if (lane == 0) mbar_arrive(bar_pub + 8 * wg);
            if (tid == 0) { TL(2, 3); TC(2, 3); }
            float s0 = 0.f, s1 = 0.f;
#pragma unroll
            for (int j = 0; j < 9; j++) { s0 += bf_lo(hw[2 * j]) + bf_hi(hw[2 * j]); s1 += bf_lo(hw[2 * j + 1]) + bf_hi(hw[2 * j + 1]); }
            s0 += __shfl_xor_sync(~0u, s0, 1); s0 += __shfl_xor_sync(~0u, s0, 2);
            s1 += __shfl_xor_sync(~0u, s1, 1); s1 += __shfl_xor_sync(~0u, s1, 2);
            const float m0 = s0 * (1.f / 72), m1 = s1 * (1.f / 72);
            float q0 = 0.f, q1 = 0.f;
#pragma unroll
            for (int j = 0; j < 9; j++) {
                const float a = bf_lo(hw[2 * j]) - m0, b = bf_hi(hw[2 * j]) - m0, c = bf_lo(hw[2 * j + 1]) - m1, d = bf_hi(hw[2 * j + 1]) - m1;
                q0 += a * a + b * b; q1 += c * c + d * d;
            }
            q0 += __shfl_xor_sync(~0u, q0, 1); q0 += __shfl_xor_sync(~0u, q0, 2);
            q1 += __shfl_xor_sync(~0u, q1, 1); q1 += __shfl_xor_sync(~0u, q1, 2);
            if (t == 0) {
                const uint32_t a = sb + C_OFF_HST + (warp * 16 + r) * 8;
                sts64f(a, s0, q0); sts64f(a + 64, s1, q1);
            }
            mbar_wait(bar_hrd, 0);
            __syncwarp();
            if (lane == 0) mbar_arrive(bar_pub + 8 * wg);
        }
        uint32_t hreg[128];
        const uint32_t s_hx = sb + wg * C_HALF + ((e + 1) & 7) * 8192;
        float rstd0, rstd1;
        uint32_t mf0, mf1;
        uint32_t ph = 0;
        const uint32_t a_lo = desc_addr(sb + wg * C_HALF) | ((1024 >> 4) << 16);
#pragma unroll
        for (int pass = 0; pass < 3; pass++) {
            if (STAGGER >= 0 && wg == 1) nbar_sync(4, 256);
            float acc[96];
            float2 hs[4];
            const uint32_t b_lo = desc_addr(sb + C_OFF_W) | ((2048 >> 4) << 16);
#pragma unroll 1
            for (int i = 0; i < 3; i++) {
#pragma unroll
                for (int st = 0; st < 12; st++) {
                    if (pass == 0) {
                        const int n = 12 * i + st;
                        if ((2 * n + 1) / 9 != (2 * n - 1) / 9 || n == 0) mbar_wait(bar_h + 8 * ((2 * n + 1) / 9), 0);
                    }
                    mbar_wait(bar_full + 8 * st, ph);
                    if (tid == TCT && !(st & 1)) TC(2, 16 + pass * 18 + i * 6 + st / 2);
                    if (pass == 0 && st == 0 && i == 0 && tid == 0) TL(2, 5);
                    wg_fence();
                    mma_ss_n192(acc, a_lo + (12 * i + st) * 128, 128 >> 4, b_lo + st * (C_SLOT >> 4), HI_SW128, st > 0 ? 1u : (uint32_t)i);
                    wg_commit();
                    if (arm) mbar_expect(bar_full + 8 * st, C_SLOT);
                    if (st == STAGGER && wg == 0 && i == 0) nbar_arrive(4, 256);
                    if (pass == 0 && st == 0 && i == 2) {
                        mbar_wait(bar_hst, 0);
                        const float2* p = g_hstat + 2 * t * SEQ + rb * 128 + warp * 16 + r;
                        asm volatile("ld.global.cg.v2.f32 {%0, %1}, [%2];" : "=f"(hs[0].x), "=f"(hs[0].y) : "l"(p));
                        asm volatile("ld.global.cg.v2.f32 {%0, %1}, [%2];" : "=f"(hs[1].x), "=f"(hs[1].y) : "l"(p + SEQ));
                        asm volatile("ld.global.cg.v2.f32 {%0, %1}, [%2];" : "=f"(hs[2].x), "=f"(hs[2].y) : "l"(p + 8));
                        asm volatile("ld.global.cg.v2.f32 {%0, %1}, [%2];" : "=f"(hs[3].x), "=f"(hs[3].y) : "l"(p + SEQ + 8));
                    }
                    wg_wait<LAG>();
                    if ((((st + LAG) & 1) ? rel_odd : rel_even) && (st >= LAG || i > 0)) mbar_arrive_cluster(rel + 8 * ((st + 12 - LAG) % 12));
                }
                ph ^= 1;
            }
            if (pass == 0) {
                const RowStat s0 = combine_hstat(hs[0], hs[1]), s1 = combine_hstat(hs[2], hs[3]);
                rstd0 = s0.rstd; rstd1 = s1.rstd;
                mf0 = mean_frag(s0.mean, t); mf1 = mean_frag(s1.mean, t);
                mbar_wait(bar_cs, 0);
            }
            wg_fence();
            mma_rs_n192(acc, mf0, mf1, 0u, 0u, desc_addr(sb + C_OFF_CS) + pass * 192, 128 >> 4);
            wg_commit();
            if (LAG == 2) { wg_wait<2>(); if (rel_even) mbar_arrive_cluster(rel + 8 * 10); }
            wg_wait<1>();
            if (rel_odd) mbar_arrive_cluster(rel + 8 * 11);
            wg_wait<0>();
            fence_regs(acc);
            if (pass == 2 && rel_even) mbar_arrive(bar_g1);
            if (tid == 0) TL(2, 6 + pass);
#pragma unroll
            for (int j = 0; j < 48; j++) {
                const uint32_t w = pack_bf16_relu(acc[2 * j], acc[2 * j + 1]);
                if (pass * 48 + j < 128) hreg[(pass * 48 + j) & 127] = w;
                else sts32(s_hx + ((j - 32) >> 1) * 1024 + (warp & 3) * 256 + (j & 1) * 128 + lane * 4, w);
            }
        }
        fence_async_smem();
        nbar_sync(2 + wg, 128);
        fence_regs(hreg);
        const uint32_t b_lo = desc_addr(sb + C_OFF_W) | (1u << 16);
        const uint32_t stg = sb + wg * C_HALF + 65536;
        const uint32_t hx_lo = desc_addr(s_hx) | ((1024 >> 4) << 16);
        float acc0[32], acc1[32];
        auto gemm2_pass = [&](auto kind_tag, int p, float (&acc)[32], float (&prev)[32]) {
            constexpr int KIND = decltype(kind_tag)::value;
#pragma unroll
            for (int st = 0; st < 12; st++) {
                mbar_wait(bar_full + 8 * st, KIND != 1);
                if (tid == TCT && !(st & 1)) TC(2, 70 + p * 6 + st / 2);
                wg_fence();
#pragma unroll
                for (int j = 0; j < 3; j++) {
                    const int kk = st * 3 + j;
                    const uint32_t bl = b_lo + st * (C_SLOT >> 4) + j * 128;
                    if (kk < 32) mma_rs_n64(acc, hreg[(4 * kk) & 127], hreg[(4 * kk + 1) & 127], hreg[(4 * kk + 2) & 127], hreg[(4 * kk + 3) & 127], bl, HI_SW128, kk > 0 ? 1u : 0u);
                    else mma_ss_n64(acc, hx_lo + (kk - 32) * 128, 128 >> 4, bl, HI_SW128);
                }
                wg_commit();
                if (KIND < 2 && arm) mbar_expect(bar_full + 8 * st, C_SLOT);
                if (KIND == 2 && st >= 5 && st < 11) {
                    if (st == 5) {
                        mbar_wait(bar_recv, 0);
#pragma unroll
                        for (int i = 0; i < 32; i++) prev[i] = 0.f;
                    }
                    add_partial(prev, sb + wg * C_HALF + ((e + 4 - st) & 7) * 8192 + (warp & 3) * 2048 + lane * 16);
                }
                if (st >= LAG || KIND == 1) wg_wait<LAG>();
                if ((st >= LAG ? KIND < 2 : KIND == 1) && (((st + LAG) & 1) ? rel_odd : rel_even)) mbar_arrive_cluster(rel + 8 * ((st + 12 - LAG) % 12));
                if (st == LAG - 1 && (KIND > 0 || p > 0)) {
                    fence_regs(prev);
                    if (p == 1) mbar_wait(bar_g1, 0); else mbar_wait(bar_sfree + 8 * wg, KIND & 1);
#pragma unroll
                    for (int i = 0; i < 4; i++)
                        sts128(stg + (warp & 3) * 2048 + i * 512 + lane * 16, pack_bf16(prev[8 * i], prev[8 * i + 1]), pack_bf16(prev[8 * i + 2], prev[8 * i + 3]),
                               pack_bf16(prev[8 * i + 4], prev[8 * i + 5]), pack_bf16(prev[8 * i + 6], prev[8 * i + 7]));
                    __syncwarp();
                    if (lane == 0) mbar_arrive(bar_pub + 8 * wg);
                }
            }
        };
#pragma unroll 1
        for (int p = 0; p < 8; p += 2) {
            gemm2_pass(std::integral_constant<int, 0>(), p, acc0, acc1);
            gemm2_pass(std::integral_constant<int, 1>(), p + 1, acc1, acc0);
            if (LAG == 2) { wg_wait<1>(); if (rel_even) mbar_arrive_cluster(rel + 8 * 10); }
            wg_wait<0>();
            fence_regs(acc1);
            if (rel_odd) mbar_arrive_cluster(rel + 8 * 11);
        }
        gemm2_pass(std::integral_constant<int, 2>(), 8, acc0, acc1);
        float (&acc)[32] = acc0, (&sum)[32] = acc1;
        const uint32_t hb = sb + wg * C_HALF + e * 8192 + (warp & 3) * 256 + lane * 4;
        uint32_t hv[16];
#pragma unroll
        for (int j = 0; j < 8; j++) { hv[2 * j] = lds32(hb + j * 1024); hv[2 * j + 1] = lds32(hb + j * 1024 + 128); }
        if (tid == 0) { TL(2, 9); TC(2, 9); }
        mbar_wait(bar_recv + 8, 0);
        if (tid == 0) { TL(2, 10); TC(2, 10); }
        add_partial(sum, stg + (warp & 3) * 2048 + lane * 16);
        wg_wait<0>();
        fence_regs(acc);
        const uint32_t ob = stg + ((warp & 3) * 16 + r) * 128 + t * 4;
#pragma unroll
        for (int j = 0; j < 8; j++) {
            sts32(ob + ((j ^ r) << 4), pack_bf16(bf_lo(hv[2 * j]) + rstd0 * (acc[4 * j] + sum[4 * j]), bf_hi(hv[2 * j]) + rstd0 * (acc[4 * j + 1] + sum[4 * j + 1])));
            sts32(ob + ((j ^ r) << 4) + 1024, pack_bf16(bf_lo(hv[2 * j + 1]) + rstd1 * (acc[4 * j + 2] + sum[4 * j + 2]), bf_hi(hv[2 * j + 1]) + rstd1 * (acc[4 * j + 3] + sum[4 * j + 3])));
        }
        fence_async_smem();
        nbar_sync(2 + wg, 128);
        if (tid == 0) { TL(2, 11); TC(2, 11); }
        if (rel_even) {
            tma_store_2d(&tm_out, stg, e * 64, rb * 128 + wg * 64);
            bulk_commit();
            bulk_wait_read();
            TL(2, 12 + wg); TC(2, 12 + wg);
        }
    }
}

typedef CUresult (*EncodeFn)(CUtensorMap*, CUtensorMapDataType, cuuint32_t, void*, const cuuint64_t*, const cuuint64_t*,
                             const cuuint32_t*, const cuuint32_t*, CUtensorMapInterleave, CUtensorMapSwizzle,
                             CUtensorMapL2promotion, CUtensorMapFloatOOBfill);

void make_map(EncodeFn enc, CUtensorMap* m, const void* ptr, int cols, int rows, int box_c, int box_r, int chunks, CUtensorMapSwizzle sw,
              CUtensorMapL2promotion promo = CU_TENSOR_MAP_L2_PROMOTION_NONE) {
    const cuuint64_t dims[3] = {(cuuint64_t)cols, (cuuint64_t)rows, (cuuint64_t)chunks};
    const cuuint64_t strides[2] = {(cuuint64_t)cols * 2, (cuuint64_t)box_c * 2};
    const cuuint32_t box[3] = {(cuuint32_t)box_c, (cuuint32_t)box_r, (cuuint32_t)chunks};
    const cuuint32_t es[3] = {1, 1, 1};
    enc(m, CU_TENSOR_MAP_DATA_TYPE_BFLOAT16, chunks > 1 ? 3 : 2, (void*)ptr, dims, strides, box, es, CU_TENSOR_MAP_INTERLEAVE_NONE, sw,
        promo, CU_TENSOR_MAP_FLOAT_OOB_FILL_NONE);
}

}

extern "C" void kernel_launch(void* const* d_in, const int* in_sizes, int n_in, void* d_out, int out_size) {
    const __nv_bfloat16* x = (const __nv_bfloat16*)d_in[0];
    const __nv_bfloat16* wqkv = (const __nv_bfloat16*)d_in[1];
    const __nv_bfloat16* wo = (const __nv_bfloat16*)d_in[2];
    const __nv_bfloat16* w1 = (const __nv_bfloat16*)d_in[4];
    const __nv_bfloat16* w2 = (const __nv_bfloat16*)d_in[5];

    void* fn = nullptr;
    cudaDriverEntryPointQueryResult qr;
    cudaGetDriverEntryPoint("cuTensorMapEncodeTiled", &fn, cudaEnableDefault, &qr);
    EncodeFn enc = (EncodeFn)fn;
    void* p_attn = nullptr;
    cudaGetSymbolAddress(&p_attn, g_attn);
    CUtensorMap tm_x, tm_wqkv, tm_wo, tm_wo2, tm_attn, tm_w1, tm_w2, tm_out;
    make_map(enc, &tm_x, x, DM, SEQ, 64, 128, 1, CU_TENSOR_MAP_SWIZZLE_128B, PROMO_X);
    make_map(enc, &tm_wqkv, wqkv, 1728, DM, 32, 16, 7, CU_TENSOR_MAP_SWIZZLE_64B, PROMO_W);
    {
        const cuuint64_t dims[4] = {DM, 16, 9, 32}, strides[3] = {DM * 2, 16, 18 * DM * 2};
        const cuuint32_t box[4] = {8, 16, 9, 16}, es[5] = {1, 1, 1, 1, 1};
        enc(&tm_wo, CU_TENSOR_MAP_DATA_TYPE_BFLOAT16, 4, (void*)wo, dims, strides, box, es, CU_TENSOR_MAP_INTERLEAVE_NONE,
            CU_TENSOR_MAP_SWIZZLE_NONE, CU_TENSOR_MAP_L2_PROMOTION_NONE, CU_TENSOR_MAP_FLOAT_OOB_FILL_NONE);
        const cuuint64_t dims2[5] = {DM, 2, 8, 9, 4}, strides2[4] = {DM * 2, 18 * DM * 2, 16, 144 * DM * 2};
        const cuuint32_t box2[5] = {8, 2, 8, 9, 4};
        enc(&tm_wo2, CU_TENSOR_MAP_DATA_TYPE_BFLOAT16, 5, (void*)(wo + 16 * DM), dims2, strides2, box2, es, CU_TENSOR_MAP_INTERLEAVE_NONE,
            CU_TENSOR_MAP_SWIZZLE_NONE, CU_TENSOR_MAP_L2_PROMOTION_NONE, CU_TENSOR_MAP_FLOAT_OOB_FILL_NONE);
    }
    make_map(enc, &tm_attn, p_attn, DM, SEQ, 64, 64, 1, CU_TENSOR_MAP_SWIZZLE_128B);
    make_map(enc, &tm_w1, w1, FF, DM, 64, 16, 3, CU_TENSOR_MAP_SWIZZLE_128B);
    make_map(enc, &tm_w2, w2, DM, FF, 64, 48, 1, CU_TENSOR_MAP_SWIZZLE_128B);
    make_map(enc, &tm_out, d_out, DM, SEQ, 64, 64, 1, CU_TENSOR_MAP_SWIZZLE_128B);

    cudaFuncSetAttribute(qkv_kernel, cudaFuncAttributeMaxDynamicSharedMemorySize, A_SMEM);
    cudaFuncSetAttribute(attn_kernel, cudaFuncAttributeMaxDynamicSharedMemorySize, B_SMEM);
    cudaFuncSetAttribute(ffn_kernel, cudaFuncAttributeMaxDynamicSharedMemorySize, C_SMEM);

    cudaLaunchAttribute at[2];
    at[0].id = cudaLaunchAttributeClusterDimension;
    at[0].val.clusterDim.x = 2; at[0].val.clusterDim.y = 1; at[0].val.clusterDim.z = 1;
    at[1].id = cudaLaunchAttributeProgrammaticStreamSerialization;
    at[1].val.programmaticStreamSerializationAllowed = 1;

    cudaLaunchConfig_t cfg = {};
    cfg.stream = cudaStreamPerThread;
    cfg.gridDim = 128; cfg.blockDim = 384; cfg.dynamicSmemBytes = A_SMEM; cfg.attrs = at; cfg.numAttrs = 1;
    cudaLaunchKernelEx(&cfg, qkv_kernel, tm_x, tm_wqkv, x);
    cfg.gridDim = 132; cfg.blockDim = 512; cfg.dynamicSmemBytes = B_SMEM; cfg.attrs = at + 1; cfg.numAttrs = 1;
    cudaLaunchKernelEx(&cfg, attn_kernel, tm_wo, tm_wo2, w1, w2);
    cfg.gridDim = 128; cfg.blockDim = 384; cfg.dynamicSmemBytes = C_SMEM; cfg.attrs = at; cfg.numAttrs = 2;
    cudaLaunchKernelEx(&cfg, ffn_kernel, tm_attn, tm_w1, tm_w2, tm_out, x, (__nv_bfloat16*)d_out);
}
```

```cpp
#include <cuda_runtime.h>
#include <cuda_bf16.h>
#include <cuda.h>
#include <stdint.h>
#include <type_traits>

#define PROMO_X CU_TENSOR_MAP_L2_PROMOTION_NONE
#define PROMO_W CU_TENSOR_MAP_L2_PROMOTION_NONE
#define STAGGER -1
#define LAG 1
#define W2PF 3
#define HELPER_PF 0
#define REM_AT 2
#define CHAINS 1
#define sum1 sum
#define SQ1 sq
#define WFENCE 1
#define XWAIT 1
#define TCT 0
namespace {

constexpr int SEQ = 2048, DM = 576, FF = 4608;
constexpr float LN_EPS = 1e-5f;
constexpr float QSCALE = 0.34004428f;

constexpr int BLK_BYTES = 6144;
constexpr int SLOT_BYTES = 16 * BLK_BYTES;
#define PATTERN 0xB5B5u
constexpr uint32_t POLY_PATTERN = PATTERN;

__device__ __align__(1024) uint8_t g_qkv[96 * SLOT_BYTES];
__device__ __align__(1024) __nv_bfloat16 g_attn[SEQ * 512];
__device__ __align__(1024) uint32_t g_rem[32 * SEQ];
__device__ __align__(1024) uint8_t g_h[16 * 147456];
__device__ __align__(1024) uint8_t g_wo_img[8 * 82944];
__device__ __align__(1024) uint8_t g_part[16 * 9 * 8 * 16384];
__device__ __align__(128) float g_cs0[8 * 16 * 216];
__device__ __align__(128) uint8_t g_cs1[FF / 8 * 128];
__device__ __align__(128) float2 g_xstat[SEQ];
__device__ __align__(128) float2 g_hstat[8 * SEQ];
__device__ __align__(16) float g_kmax[8 * 128];
constexpr int FLAG_H = 0, FLAG_HST = 128, FLAG_PART = 144, FLAG_WO = FLAG_PART + 16 * 9 * 8, N_FLAG_C = FLAG_WO + 8;
static_assert(N_FLAG_C <= 128 * 12, "kernel A clears 12 flags per CTA");
__device__ unsigned int g_flag_c[N_FLAG_C];

#define TL(k, id)
#define TC(k, id)
constexpr uint32_t SPIN_LIMIT = 1u << 18;
#define SUSPEND_NS 20u

__device__ __forceinline__ uint32_t smem_u32(const void* p) { return (uint32_t)__cvta_generic_to_shared(p); }
__device__ __forceinline__ void mbar_init(uint32_t bar, uint32_t cnt) { asm volatile("mbarrier.init.shared::cta.b64 [%0], %1;" :: "r"(bar), "r"(cnt) : "memory"); }
__device__ __forceinline__ void mbar_expect(uint32_t bar, uint32_t bytes) { asm volatile("mbarrier.arrive.expect_tx.shared::cta.b64 _, [%0], %1;" :: "r"(bar), "r"(bytes) : "memory"); }
__device__ __forceinline__ void mbar_arrive(uint32_t bar) { asm volatile("mbarrier.arrive.shared::cta.b64 _, [%0];" :: "r"(bar) : "memory"); }
__device__ __forceinline__ void mbar_arrive_cluster(uint32_t bar) { asm volatile("mbarrier.arrive.shared::cluster.b64 _, [%0];" :: "r"(bar) : "memory"); }
__device__ __forceinline__ void mbar_wait(uint32_t bar, uint32_t parity) {
    asm volatile("{\n.reg .pred p, q;\n.reg .u32 n;\n"
                 "mbarrier.try_wait.parity.shared::cta.b64 p, [%0], %1;\n@p bra.uni WAIT_DONE;\nmov.u32 n, 0;\n"
                 "WAIT_LOOP:\nmbarrier.try_wait.parity.shared::cta.b64 p, [%0], %1;\nadd.u32 n, n, 1;\nsetp.gt.or.u32 q, n, %2, p;\n@!q bra.uni WAIT_LOOP;\n"
                 "WAIT_DONE:\n}\n" :: "r"(bar), "r"(parity), "n"(SPIN_LIMIT) : "memory");
}
__device__ __forceinline__ void mbar_wait_trap(uint32_t bar, uint32_t parity) {
    for (uint32_t i = 0;; i++) {
        uint32_t ok;
        asm volatile("{\n.reg .pred p;\nmbarrier.try_wait.parity.shared::cta.b64 p, [%1], %2, %3;\nselp.u32 %0, 1, 0, p;\n}\n"
                     : "=r"(ok) : "r"(bar), "r"(parity), "r"(SUSPEND_NS) : "memory");
        if (ok) break;
        if (i > SPIN_LIMIT) __trap();
    }
}
__device__ __forceinline__ uint32_t mapa(uint32_t addr, uint32_t rank) { uint32_t r; asm("mapa.shared::cluster.u32 %0, %1, %2;" : "=r"(r) : "r"(addr), "r"(rank)); return r; }
__device__ __forceinline__ void cluster_sync() { asm volatile("barrier.cluster.arrive.relaxed.aligned;\nbarrier.cluster.wait.aligned;" ::: "memory"); }
__device__ __forceinline__ void fence_mbar_init() { asm volatile("fence.mbarrier_init.release.cluster;" ::: "memory"); }
__device__ __forceinline__ void fence_async_smem() { asm volatile("fence.proxy.async.shared::cta;" ::: "memory"); }
__device__ __forceinline__ void nbar_sync(uint32_t id, uint32_t n) { asm volatile("bar.sync %0, %1;" :: "r"(id), "r"(n) : "memory"); }
__device__ __forceinline__ void nbar_arrive(uint32_t id, uint32_t n) { asm volatile("bar.arrive %0, %1;" :: "r"(id), "r"(n) : "memory"); }
__device__ __forceinline__ void pdl_wait() { asm volatile("griddepcontrol.wait;" ::: "memory"); }
__device__ __forceinline__ void pdl_launch() { asm volatile("griddepcontrol.launch_dependents;" ::: "memory"); }
__device__ __forceinline__ void flag_add(unsigned int* p) {
    asm volatile("fence.proxy.async.global;\nred.release.gpu.global.add.u32 [%0], 1;" :: "l"(p) : "memory");
}
__device__ __forceinline__ void flag_acquire() { asm volatile("fence.acquire.gpu;\nfence.proxy.async.global;" ::: "memory"); }
__device__ __forceinline__ uint32_t flag_read(const unsigned int* p) {
    uint32_t v;
    asm volatile("ld.relaxed.gpu.global.u32 %0, [%1];" : "=r"(v) : "l"(p) : "memory");
    return v;
}
__device__ __forceinline__ void st_strong(void* p, uint32_t a, uint32_t b) { asm volatile("st.relaxed.gpu.global.v2.b32 [%0], {%1, %2};" :: "l"(p), "r"(a), "r"(b) : "memory"); }
__device__ __forceinline__ uint4 ld_strong(const void* p) {
    uint4 v;
    asm volatile("ld.relaxed.gpu.global.v4.b32 {%0, %1, %2, %3}, [%4];" : "=r"(v.x), "=r"(v.y), "=r"(v.z), "=r"(v.w) : "l"(p) : "memory");
    return v;
}
__device__ __forceinline__ void flag_wait(const unsigned int* p, uint32_t target) {
    for (uint32_t i = 0; flag_read(p) < target; i++) if (i > SPIN_LIMIT) __trap();
    flag_acquire();
}
__device__ __forceinline__ uint32_t flag_poll(const unsigned int* p, bool active, uint32_t target) {
    return __ballot_sync(~0u, active && flag_read(p) >= target);
}
__device__ __forceinline__ void bulk_load(uint32_t dst, const void* src, uint32_t bytes, uint32_t bar) {
    asm volatile("cp.async.bulk.shared::cluster.global.mbarrier::complete_tx::bytes [%0], [%1], %2, [%3];" :: "r"(dst), "l"(src), "r"(bytes), "r"(bar) : "memory");
}
__device__ __forceinline__ void bulk_store(void* dst, uint32_t src, uint32_t bytes) {
    asm volatile("cp.async.bulk.global.shared::cta.bulk_group [%0], [%1], %2;" :: "l"(dst), "r"(src), "r"(bytes) : "memory");
}
__device__ __forceinline__ void bulk_commit() { asm volatile("cp.async.bulk.commit_group;" ::: "memory"); }
__device__ __forceinline__ void bulk_wait_all() { asm volatile("cp.async.bulk.wait_group 0;" ::: "memory"); }
__device__ __forceinline__ void l2_prefetch(const void* src, uint32_t bytes) { asm volatile("cp.async.bulk.prefetch.L2.global [%0], %1;" :: "l"(src), "r"(bytes) : "memory"); }
__device__ __forceinline__ void tma_2d(uint32_t dst, const CUtensorMap* m, int c0, int c1, uint32_t bar) {
    asm volatile("cp.async.bulk.tensor.2d.shared::cluster.global.mbarrier::complete_tx::bytes [%0], [%1, {%3, %4}], [%2];"
                 :: "r"(dst), "l"(m), "r"(bar), "r"(c0), "r"(c1) : "memory");
}
__device__ __forceinline__ void tma_2d_mc(uint32_t dst, const CUtensorMap* m, int c0, int c1, uint32_t bar) {
    asm volatile("cp.async.bulk.tensor.2d.shared::cluster.global.mbarrier::complete_tx::bytes.multicast::cluster [%0], [%1, {%3, %4}], [%2], %5;"
                 :: "r"(dst), "l"(m), "r"(bar), "r"(c0), "r"(c1), "h"((uint16_t)3) : "memory");
}
__device__ __forceinline__ void tma_3d_mc(uint32_t dst, const CUtensorMap* m, int c0, int c1, uint32_t bar) {
    asm volatile("cp.async.bulk.tensor.3d.shared::cluster.global.mbarrier::complete_tx::bytes.multicast::cluster [%0], [%1, {%3, %4, %5}], [%2], %6;"
                 :: "r"(dst), "l"(m), "r"(bar), "r"(c0), "r"(c1), "r"(0), "h"((uint16_t)3) : "memory");
}
__device__ __forceinline__ void tma_store_2d(const CUtensorMap* m, uint32_t src, int c0, int c1) {
    asm volatile("cp.async.bulk.tensor.2d.global.shared::cta.bulk_group [%0, {%2, %3}], [%1];" :: "l"(m), "r"(src), "r"(c0), "r"(c1) : "memory");
}
__device__ __forceinline__ void tma_prefetch_desc(const CUtensorMap* m) { asm volatile("prefetch.tensormap [%0];" :: "l"(m) : "memory"); }
__device__ __forceinline__ void wg_fence() { asm volatile("wgmma.fence.sync.aligned;" ::: "memory"); }
__device__ __forceinline__ void wg_commit() { asm volatile("wgmma.commit_group.sync.aligned;" ::: "memory"); }
template <int N> __device__ __forceinline__ void wg_wait() { asm volatile("wgmma.wait_group.sync.aligned %0;" :: "n"(N) : "memory"); }
template <int N> __device__ __forceinline__ void fence_regs(float (&d)[N]) {
#pragma unroll
    for (int i = 0; i < N; i++) asm volatile("" : "+f"(d[i]) :: "memory");
}
template <int N> __device__ __forceinline__ void fence_regs(uint32_t (&d)[N]) {
#pragma unroll
    for (int i = 0; i < N; i++) asm volatile("" : "+r"(d[i]) :: "memory");
}
__device__ __forceinline__ uint32_t pack_bf16(float lo, float hi) { uint32_t r; asm("cvt.rn.bf16x2.f32 %0, %1, %2;" : "=r"(r) : "f"(hi), "f"(lo)); return r; }
__device__ __forceinline__ uint32_t pack_bf16_relu(float lo, float hi) { uint32_t r; asm("cvt.rn.relu.bf16x2.f32 %0, %1, %2;" : "=r"(r) : "f"(hi), "f"(lo)); return r; }
__device__ __forceinline__ float bf_lo(uint32_t w) { return __uint_as_float(w << 16); }
__device__ __forceinline__ float bf_hi(uint32_t w) { return __uint_as_float(w & 0xFFFF0000u); }
__device__ __forceinline__ float ex2(float x) { float r; asm("ex2.approx.ftz.f32 %0, %1;" : "=f"(r) : "f"(x)); return r; }
__device__ __forceinline__ void sts32(uint32_t a, uint32_t v) { asm volatile("st.shared.b32 [%0], %1;" :: "r"(a), "r"(v) : "memory"); }
__device__ __forceinline__ void sts64f(uint32_t a, float x, float y) { asm volatile("st.shared.v2.f32 [%0], {%1, %2};" :: "r"(a), "f"(x), "f"(y) : "memory"); }
__device__ __forceinline__ void sts128(uint32_t a, uint32_t x, uint32_t y, uint32_t z, uint32_t w) { asm volatile("st.shared.v4.b32 [%0], {%1, %2, %3, %4};" :: "r"(a), "r"(x), "r"(y), "r"(z), "r"(w) : "memory"); }
__device__ __forceinline__ uint32_t lds32(uint32_t a) { uint32_t v; asm volatile("ld.shared.b32 %0, [%1];" : "=r"(v) : "r"(a) : "memory"); return v; }
__device__ __forceinline__ float2 lds64f(uint32_t a) { float2 v; asm volatile("ld.shared.v2.f32 {%0, %1}, [%2];" : "=f"(v.x), "=f"(v.y) : "r"(a) : "memory"); return v; }
__device__ __forceinline__ uint4 lds128(uint32_t a) { uint4 v; asm volatile("ld.shared.v4.b32 {%0, %1, %2, %3}, [%4];" : "=r"(v.x), "=r"(v.y), "=r"(v.z), "=r"(v.w) : "r"(a) : "memory"); return v; }

__device__ __forceinline__ uint32_t desc_addr(uint32_t a) { return (a & 0x3FFFFu) >> 4; }
constexpr uint32_t HI_SW128 = (1024 >> 4) | (1u << 30);
constexpr uint32_t HI_SW64 = (512 >> 4) | (2u << 30);

__device__ __forceinline__ void mma_ss_n224(float (&d)[112], uint32_t alo, uint32_t ahi, uint32_t blo, uint32_t bhi, uint32_t acc) {
    asm volatile("{\n.reg .b64 da, db;\n.reg .pred p;\nsetp.ne.u32 p, %116, 0;\nmov.b64 da, {%112, %113};\nmov.b64 db, {%114, %115};\n"
        "wgmma.mma_async.sync.aligned.m64n224k16.f32.bf16.bf16 "
        "{%0, %1, %2, %3, %4, %5, %6, %7, %8, %9, %10, %11, %12, %13, %14, %15, "
        "%16, %17, %18, %19, %20, %21, %22, %23, %24, %25, %26, %27, %28, %29, %30, %31, "
        "%32, %33, %34, %35, %36, %37, %38, %39, %40, %41, %42, %43, %44, %45, %46, %47, "
        "%48, %49, %50, %51, %52, %53, %54, %55, %56, %57, %58, %59, %60, %61, %62, %63, "
        "%64, %65, %66, %67, %68, %69, %70, %71, %72, %73, %74, %75, %76, %77, %78, %79, "
        "%80, %81, %82, %83, %84, %85, %86, %87, %88, %89, %90, %91, %92, %93, %94, %95, "
        "%96, %97, %98, %99, %100, %101, %102, %103, %104, %105, %106, %107, %108, %109, %110, %111}, "
        "da, db, p, 1, 1, 0, 1;\n}\n"
        : "+f"(d[0]), "+f"(d[1]), "+f"(d[2]), "+f"(d[3]), "+f"(d[4]), "+f"(d[5]), "+f"(d[6]), "+f"(d[7]),
          "+f"(d[8]), "+f"(d[9]), "+f"(d[10]), "+f"(d[11]), "+f"(d[12]), "+f"(d[13]), "+f"(d[14]), "+f"(d[15]),
          "+f"(d[16]), "+f"(d[17]), "+f"(d[18]), "+f"(d[19]), "+f"(d[20]), "+f"(d[21]), "+f"(d[22]), "+f"(d[23]),
          "+f"(d[24]), "+f"(d[25]), "+f"(d[26]), "+f"(d[27]), "+f"(d[28]), "+f"(d[29]), "+f"(d[30]), "+f"(d[31]),
          "+f"(d[32]), "+f"(d[33]), "+f"(d[34]), "+f"(d[35]), "+f"(d[36]), "+f"(d[37]), "+f"(d[38]), "+f"(d[39]),
          "+f"(d[40]), "+f"(d[41]), "+f"(d[42]), "+f"(d[43]), "+f"(d[44]), "+f"(d[45]), "+f"(d[46]), "+f"(d[47]),
          "+f"(d[48]), "+f"(d[49]), "+f"(d[50]), "+f"(d[51]), "+f"(d[52]), "+f"(d[53]), "+f"(d[54]), "+f"(d[55]),
          "+f"(d[56]), "+f"(d[57]), "+f"(d[58]), "+f"(d[59]), "+f"(d[60]), "+f"(d[61]), "+f"(d[62]), "+f"(d[63]),
          "+f"(d[64]), "+f"(d[65]), "+f"(d[66]), "+f"(d[67]), "+f"(d[68]), "+f"(d[69]), "+f"(d[70]), "+f"(d[71]),
          "+f"(d[72]), "+f"(d[73]), "+f"(d[74]), "+f"(d[75]), "+f"(d[76]), "+f"(d[77]), "+f"(d[78]), "+f"(d[79]),
          "+f"(d[80]), "+f"(d[81]), "+f"(d[82]), "+f"(d[83]), "+f"(d[84]), "+f"(d[85]), "+f"(d[86]), "+f"(d[87]),
          "+f"(d[88]), "+f"(d[89]), "+f"(d[90]), "+f"(d[91]), "+f"(d[92]), "+f"(d[93]), "+f"(d[94]), "+f"(d[95]),
          "+f"(d[96]), "+f"(d[97]), "+f"(d[98]), "+f"(d[99]), "+f"(d[100]), "+f"(d[101]), "+f"(d[102]), "+f"(d[103]),
          "+f"(d[104]), "+f"(d[105]), "+f"(d[106]), "+f"(d[107]), "+f"(d[108]), "+f"(d[109]), "+f"(d[110]), "+f"(d[111])
        : "r"(alo), "r"(ahi), "r"(blo), "r"(bhi), "r"(acc));
}
__device__ __forceinline__ void mma_qk_first(float (&d)[32], uint32_t a0, uint32_t a1, uint32_t a2, uint32_t a3, uint64_t db) {
    asm volatile("wgmma.mma_async.sync.aligned.m64n64k16.f32.bf16.bf16 "
        "{%0, %1, %2, %3, %4, %5, %6, %7, %8, %9, %10, %11, %12, %13, %14, %15, "
        "%16, %17, %18, %19, %20, %21, %22, %23, %24, %25, %26, %27, %28, %29, %30, %31}, "
        "{%32, %33, %34, %35}, %36, 0, 1, 1, 0;"
        : "=f"(d[0]), "=f"(d[1]), "=f"(d[2]), "=f"(d[3]), "=f"(d[4]), "=f"(d[5]), "=f"(d[6]), "=f"(d[7]),
          "=f"(d[8]), "=f"(d[9]), "=f"(d[10]), "=f"(d[11]), "=f"(d[12]), "=f"(d[13]), "=f"(d[14]), "=f"(d[15]),
          "=f"(d[16]), "=f"(d[17]), "=f"(d[18]), "=f"(d[19]), "=f"(d[20]), "=f"(d[21]), "=f"(d[22]), "=f"(d[23]),
          "=f"(d[24]), "=f"(d[25]), "=f"(d[26]), "=f"(d[27]), "=f"(d[28]), "=f"(d[29]), "=f"(d[30]), "=f"(d[31])
        : "r"(a0), "r"(a1), "r"(a2), "r"(a3), "l"(db));
}
__device__ __forceinline__ void mma_qk_second(float (&d)[32], uint32_t a0, uint32_t a1, uint32_t a2, uint32_t a3, uint64_t db) {
    asm volatile("wgmma.mma_async.sync.aligned.m64n64k16.f32.bf16.bf16 "
        "{%0, %1, %2, %3, %4, %5, %6, %7, %8, %9, %10, %11, %12, %13, %14, %15, "
        "%16, %17, %18, %19, %20, %21, %22, %23, %24, %25, %26, %27, %28, %29, %30, %31}, "
        "{%32, %33, %34, %35}, %36, 1, 1, 1, 0;"
        : "+f"(d[0]), "+f"(d[1]), "+f"(d[2]), "+f"(d[3]), "+f"(d[4]), "+f"(d[5]), "+f"(d[6]), "+f"(d[7]),
          "+f"(d[8]), "+f"(d[9]), "+f"(d[10]), "+f"(d[11]), "+f"(d[12]), "+f"(d[13]), "+f"(d[14]), "+f"(d[15]),
          "+f"(d[16]), "+f"(d[17]), "+f"(d[18]), "+f"(d[19]), "+f"(d[20]), "+f"(d[21]), "+f"(d[22]), "+f"(d[23]),
          "+f"(d[24]), "+f"(d[25]), "+f"(d[26]), "+f"(d[27]), "+f"(d[28]), "+f"(d[29]), "+f"(d[30]), "+f"(d[31])
        : "r"(a0), "r"(a1), "r"(a2), "r"(a3), "l"(db));
}
__device__ __forceinline__ void mma_pv(float (&d)[12], uint32_t a0, uint32_t a1, uint32_t a2, uint32_t a3, uint64_t db) {
    asm volatile("wgmma.mma_async.sync.aligned.m64n24k16.f32.bf16.bf16 "
        "{%0, %1, %2, %3, %4, %5, %6, %7, %8, %9, %10, %11}, "
        "{%12, %13, %14, %15}, %16, 1, 1, 1, 1;"
        : "+f"(d[0]), "+f"(d[1]), "+f"(d[2]), "+f"(d[3]), "+f"(d[4]), "+f"(d[5]), "+f"(d[6]), "+f"(d[7]),
          "+f"(d[8]), "+f"(d[9]), "+f"(d[10]), "+f"(d[11])
        : "r"(a0), "r"(a1), "r"(a2), "r"(a3), "l"(db));
}
__device__ __forceinline__ void mma_ss_n72(float (&d)[36], uint32_t alo, uint32_t ahi, uint32_t blo, uint32_t bhi, uint32_t acc) {
    asm volatile("{\n.reg .b64 da, db;\n.reg .pred p;\nsetp.ne.u32 p, %40, 0;\nmov.b64 da, {%36, %37};\nmov.b64 db, {%38, %39};\n"
        "wgmma.mma_async.sync.aligned.m64n72k16.f32.bf16.bf16 "
        "{%0, %1, %2, %3, %4, %5, %6, %7, %8, %9, %10, %11, %12, %13, %14, %15, "
        "%16, %17, %18, %19, %20, %21, %22, %23, %24, %25, %26, %27, %28, %29, %30, %31, "
        "%32, %33, %34, %35}, "
        "da, db, p, 1, 1, 0, 1;\n}\n"
        : "+f"(d[0]), "+f"(d[1]), "+f"(d[2]), "+f"(d[3]), "+f"(d[4]), "+f"(d[5]), "+f"(d[6]), "+f"(d[7]),
          "+f"(d[8]), "+f"(d[9]), "+f"(d[10]), "+f"(d[11]), "+f"(d[12]), "+f"(d[13]), "+f"(d[14]), "+f"(d[15]),
          "+f"(d[16]), "+f"(d[17]), "+f"(d[18]), "+f"(d[19]), "+f"(d[20]), "+f"(d[21]), "+f"(d[22]), "+f"(d[23]),
          "+f"(d[24]), "+f"(d[25]), "+f"(d[26]), "+f"(d[27]), "+f"(d[28]), "+f"(d[29]), "+f"(d[30]), "+f"(d[31]),
          "+f"(d[32]), "+f"(d[33]), "+f"(d[34]), "+f"(d[35])
        : "r"(alo), "r"(ahi), "r"(blo), "r"(bhi), "r"(acc));
}
__device__ __forceinline__ void mma_ss_n192(float (&d)[96], uint32_t alo, uint32_t ahi, uint32_t blo, uint32_t bhi, uint32_t acc) {
    asm volatile("{\n.reg .b64 da, db;\n.reg .pred p;\nsetp.ne.u32 p, %100, 0;\nmov.b64 da, {%96, %97};\nmov.b64 db, {%98, %99};\n"
        "wgmma.mma_async.sync.aligned.m64n192k16.f32.bf16.bf16 "
        "{%0, %1, %2, %3, %4, %5, %6, %7, %8, %9, %10, %11, %12, %13, %14, %15, "
        "%16, %17, %18, %19, %20, %21, %22, %23, %24, %25, %26, %27, %28, %29, %30, %31, "
        "%32, %33, %34, %35, %36, %37, %38, %39, %40, %41, %42, %43, %44, %45, %46, %47, "
        "%48, %49, %50, %51, %52, %53, %54, %55, %56, %57, %58, %59, %60, %61, %62, %63, "
        "%64, %65, %66, %67, %68, %69, %70, %71, %72, %73, %74, %75, %76, %77, %78, %79, "
        "%80, %81, %82, %83, %84, %85, %86, %87, %88, %89, %90, %91, %92, %93, %94, %95}, "
        "da, db, p, 1, 1, 0, 1;\n}\n"
        : "+f"(d[0]), "+f"(d[1]), "+f"(d[2]), "+f"(d[3]), "+f"(d[4]), "+f"(d[5]), "+f"(d[6]), "+f"(d[7]),
          "+f"(d[8]), "+f"(d[9]), "+f"(d[10]), "+f"(d[11]), "+f"(d[12]), "+f"(d[13]), "+f"(d[14]), "+f"(d[15]),
          "+f"(d[16]), "+f"(d[17]), "+f"(d[18]), "+f"(d[19]), "+f"(d[20]), "+f"(d[21]), "+f"(d[22]), "+f"(d[23]),
          "+f"(d[24]), "+f"(d[25]), "+f"(d[26]), "+f"(d[27]), "+f"(d[28]), "+f"(d[29]), "+f"(d[30]), "+f"(d[31]),
          "+f"(d[32]), "+f"(d[33]), "+f"(d[34]), "+f"(d[35]), "+f"(d[36]), "+f"(d[37]), "+f"(d[38]), "+f"(d[39]),
          "+f"(d[40]), "+f"(d[41]), "+f"(d[42]), "+f"(d[43]), "+f"(d[44]), "+f"(d[45]), "+f"(d[46]), "+f"(d[47]),
          "+f"(d[48]), "+f"(d[49]), "+f"(d[50]), "+f"(d[51]), "+f"(d[52]), "+f"(d[53]), "+f"(d[54]), "+f"(d[55]),
          "+f"(d[56]), "+f"(d[57]), "+f"(d[58]), "+f"(d[59]), "+f"(d[60]), "+f"(d[61]), "+f"(d[62]), "+f"(d[63]),
          "+f"(d[64]), "+f"(d[65]), "+f"(d[66]), "+f"(d[67]), "+f"(d[68]), "+f"(d[69]), "+f"(d[70]), "+f"(d[71]),
          "+f"(d[72]), "+f"(d[73]), "+f"(d[74]), "+f"(d[75]), "+f"(d[76]), "+f"(d[77]), "+f"(d[78]), "+f"(d[79]),
          "+f"(d[80]), "+f"(d[81]), "+f"(d[82]), "+f"(d[83]), "+f"(d[84]), "+f"(d[85]), "+f"(d[86]), "+f"(d[87]),
          "+f"(d[88]), "+f"(d[89]), "+f"(d[90]), "+f"(d[91]), "+f"(d[92]), "+f"(d[93]), "+f"(d[94]), "+f"(d[95])
        : "r"(alo), "r"(ahi), "r"(blo), "r"(bhi), "r"(acc));
}
__device__ __forceinline__ void mma_rs_n64(float (&d)[32], uint32_t a0, uint32_t a1, uint32_t a2, uint32_t a3, uint32_t blo, uint32_t bhi, uint32_t acc) {
    asm volatile("{\n.reg .b64 da, db;\n.reg .pred p;\nsetp.ne.u32 p, %38, 0;\nmov.b64 db, {%36, %37};\n"
        "wgmma.mma_async.sync.aligned.m64n64k16.f32.bf16.bf16 "
        "{%0, %1, %2, %3, %4, %5, %6, %7, %8, %9, %10, %11, %12, %13, %14, %15, "
        "%16, %17, %18, %19, %20, %21, %22, %23, %24, %25, %26, %27, %28, %29, %30, %31}, "
        "{%32, %33, %34, %35}, db, p, 1, 1, 1;\n}\n"
        : "+f"(d[0]), "+f"(d[1]), "+f"(d[2]), "+f"(d[3]), "+f"(d[4]), "+f"(d[5]), "+f"(d[6]), "+f"(d[7]),
          "+f"(d[8]), "+f"(d[9]), "+f"(d[10]), "+f"(d[11]), "+f"(d[12]), "+f"(d[13]), "+f"(d[14]), "+f"(d[15]),
          "+f"(d[16]), "+f"(d[17]), "+f"(d[18]), "+f"(d[19]), "+f"(d[20]), "+f"(d[21]), "+f"(d[22]), "+f"(d[23]),
          "+f"(d[24]), "+f"(d[25]), "+f"(d[26]), "+f"(d[27]), "+f"(d[28]), "+f"(d[29]), "+f"(d[30]), "+f"(d[31])
        : "r"(a0), "r"(a1), "r"(a2), "r"(a3), "r"(blo), "r"(bhi), "r"(acc));
}
__device__ __forceinline__ void mma_rs_n192(float (&d)[96], uint32_t a0, uint32_t a1, uint32_t a2, uint32_t a3, uint32_t blo, uint32_t bhi) {
    asm volatile("{\n.reg .b64 da, db;\nmov.b64 db, {%100, %101};\n"
        "wgmma.mma_async.sync.aligned.m64n192k16.f32.bf16.bf16 "
        "{%0, %1, %2, %3, %4, %5, %6, %7, %8, %9, %10, %11, %12, %13, %14, %15, "
        "%16, %17, %18, %19, %20, %21, %22, %23, %24, %25, %26, %27, %28, %29, %30, %31, "
        "%32, %33, %34, %35, %36, %37, %38, %39, %40, %41, %42, %43, %44, %45, %46, %47, "
        "%48, %49, %50, %51, %52, %53, %54, %55, %56, %57, %58, %59, %60, %61, %62, %63, "
        "%64, %65, %66, %67, %68, %69, %70, %71, %72, %73, %74, %75, %76, %77, %78, %79, "
        "%80, %81, %82, %83, %84, %85, %86, %87, %88, %89, %90, %91, %92, %93, %94, %95}, "
        "{%96, %97, %98, %99}, db, 1, 1, 1, 1;\n}\n"
        : "+f"(d[0]), "+f"(d[1]), "+f"(d[2]), "+f"(d[3]), "+f"(d[4]), "+f"(d[5]), "+f"(d[6]), "+f"(d[7]),
          "+f"(d[8]), "+f"(d[9]), "+f"(d[10]), "+f"(d[11]), "+f"(d[12]), "+f"(d[13]), "+f"(d[14]), "+f"(d[15]),
          "+f"(d[16]), "+f"(d[17]), "+f"(d[18]), "+f"(d[19]), "+f"(d[20]), "+f"(d[21]), "+f"(d[22]), "+f"(d[23]),
          "+f"(d[24]), "+f"(d[25]), "+f"(d[26]), "+f"(d[27]), "+f"(d[28]), "+f"(d[29]), "+f"(d[30]), "+f"(d[31]),
          "+f"(d[32]), "+f"(d[33]), "+f"(d[34]), "+f"(d[35]), "+f"(d[36]), "+f"(d[37]), "+f"(d[38]), "+f"(d[39]),
          "+f"(d[40]), "+f"(d[41]), "+f"(d[42]), "+f"(d[43]), "+f"(d[44]), "+f"(d[45]), "+f"(d[46]), "+f"(d[47]),
          "+f"(d[48]), "+f"(d[49]), "+f"(d[50]), "+f"(d[51]), "+f"(d[52]), "+f"(d[53]), "+f"(d[54]), "+f"(d[55]),
          "+f"(d[56]), "+f"(d[57]), "+f"(d[58]), "+f"(d[59]), "+f"(d[60]), "+f"(d[61]), "+f"(d[62]), "+f"(d[63]),
          "+f"(d[64]), "+f"(d[65]), "+f"(d[66]), "+f"(d[67]), "+f"(d[68]), "+f"(d[69]), "+f"(d[70]), "+f"(d[71]),
          "+f"(d[72]), "+f"(d[73]), "+f"(d[74]), "+f"(d[75]), "+f"(d[76]), "+f"(d[77]), "+f"(d[78]), "+f"(d[79]),
          "+f"(d[80]), "+f"(d[81]), "+f"(d[82]), "+f"(d[83]), "+f"(d[84]), "+f"(d[85]), "+f"(d[86]), "+f"(d[87]),
          "+f"(d[88]), "+f"(d[89]), "+f"(d[90]), "+f"(d[91]), "+f"(d[92]), "+f"(d[93]), "+f"(d[94]), "+f"(d[95])
        : "r"(a0), "r"(a1), "r"(a2), "r"(a3), "r"(blo), "r"(bhi));
}
__device__ __forceinline__ void mma_ss_n64(float (&d)[32], uint32_t alo, uint32_t ahi, uint32_t blo, uint32_t bhi) {
    asm volatile("{\n.reg .b64 da, db;\nmov.b64 da, {%32, %33};\nmov.b64 db, {%34, %35};\n"
        "wgmma.mma_async.sync.aligned.m64n64k16.f32.bf16.bf16 "
        "{%0, %1, %2, %3, %4, %5, %6, %7, %8, %9, %10, %11, %12, %13, %14, %15, "
        "%16, %17, %18, %19, %20, %21, %22, %23, %24, %25, %26, %27, %28, %29, %30, %31}, "
        "da, db, 1, 1, 1, 0, 1;\n}\n"
        : "+f"(d[0]), "+f"(d[1]), "+f"(d[2]), "+f"(d[3]), "+f"(d[4]), "+f"(d[5]), "+f"(d[6]), "+f"(d[7]),
          "+f"(d[8]), "+f"(d[9]), "+f"(d[10]), "+f"(d[11]), "+f"(d[12]), "+f"(d[13]), "+f"(d[14]), "+f"(d[15]),
          "+f"(d[16]), "+f"(d[17]), "+f"(d[18]), "+f"(d[19]), "+f"(d[20]), "+f"(d[21]), "+f"(d[22]), "+f"(d[23]),
          "+f"(d[24]), "+f"(d[25]), "+f"(d[26]), "+f"(d[27]), "+f"(d[28]), "+f"(d[29]), "+f"(d[30]), "+f"(d[31])
        : "r"(alo), "r"(ahi), "r"(blo), "r"(bhi));
}
__device__ __forceinline__ void mma_rs_n72(float (&d)[36], uint32_t a0, uint32_t a1, uint32_t a2, uint32_t a3, uint32_t blo, uint32_t bhi) {
    asm volatile("{\n.reg .b64 da, db;\nmov.b64 db, {%40, %41};\n"
        "wgmma.mma_async.sync.aligned.m64n72k16.f32.bf16.bf16 "
        "{%0, %1, %2, %3, %4, %5, %6, %7, %8, %9, %10, %11, %12, %13, %14, %15, "
        "%16, %17, %18, %19, %20, %21, %22, %23, %24, %25, %26, %27, %28, %29, %30, %31, "
        "%32, %33, %34, %35}, "
        "{%36, %37, %38, %39}, db, 1, 1, 1, 1;\n}\n"
        : "+f"(d[0]), "+f"(d[1]), "+f"(d[2]), "+f"(d[3]), "+f"(d[4]), "+f"(d[5]), "+f"(d[6]), "+f"(d[7]),
          "+f"(d[8]), "+f"(d[9]), "+f"(d[10]), "+f"(d[11]), "+f"(d[12]), "+f"(d[13]), "+f"(d[14]), "+f"(d[15]),
          "+f"(d[16]), "+f"(d[17]), "+f"(d[18]), "+f"(d[19]), "+f"(d[20]), "+f"(d[21]), "+f"(d[22]), "+f"(d[23]),
          "+f"(d[24]), "+f"(d[25]), "+f"(d[26]), "+f"(d[27]), "+f"(d[28]), "+f"(d[29]), "+f"(d[30]), "+f"(d[31]),
          "+f"(d[32]), "+f"(d[33]), "+f"(d[34]), "+f"(d[35])
        : "r"(a0), "r"(a1), "r"(a2), "r"(a3), "r"(blo), "r"(bhi));
}

constexpr int A_STAGES = 11;
constexpr uint32_t A_STAGE_BYTES = 14336;
constexpr uint32_t A_OFF_X = A_STAGES * A_STAGE_BYTES;
constexpr uint32_t A_OFF_STG = 7 * A_STAGE_BYTES;
constexpr uint32_t A_OFF_MISC = A_OFF_X + 4 * 16384;
constexpr uint32_t A_SMEM = A_OFF_MISC + 512 + 2048 + 256 + 1024;
__device__ __forceinline__ uint32_t x_slot(int kc) { return A_OFF_X + ((kc + 3) & 3) * 16384; }

__device__ __forceinline__ uint32_t absmax_bf16x2(uint32_t m, uint32_t a) {
    uint32_t r;
    asm volatile("max.xorsign.abs.bf16x2 %0, %1, %2;" : "=r"(r) : "r"(m), "r"(a));
    return r;
}

__device__ __forceinline__ void qkv_addr(uint32_t (&addr)[9], uint32_t sb, bool isv, int warp, int lane) {
#pragma unroll
    for (int j = 0; j < 9; j++) {
        const int c = 8 * j + 2 * (lane & 3), slot = c / 18, d0 = c - slot * 18;
        const int d = isv && d0 < 16 ? ((d0 & 2) << 2) | ((d0 >> 2) << 1) : d0;
        addr[j] = sb + (lane >> 2) * 16 + warp * 2 * (isv ? 384u : 128u) + slot * BLK_BYTES + (d & 7) * 2 + (d >> 3) * (isv ? 128u : 2048u);
    }
}
template <int ODD>
__device__ __forceinline__ void qkv_epilogue(const float (&acc)[112], uint32_t (&addr)[9], uint32_t sb, uint32_t s_cs, uint32_t bar_out, float2 st0, float2 st1,
                                             int ct, int rb, int warp, int lane) {
    const int t = lane & 3;
    uint32_t w[54], vmax = 0;
#pragma unroll
    for (int p = 0; p < 3; p++) {
        float2 cs[9];
#pragma unroll
        for (int j = 0; j < 9; j++) cs[j] = lds64f(s_cs + 32 * (9 * p + j + ODD) + 8 * t);
        if (p == 1 && ct == 5) qkv_addr(addr, sb, true, warp, lane);
        const uint32_t gs = ct * 3 + p >= 16 ? 384u : 128u;
        const float sc = ct * 3 + p < 8 ? QSCALE : 1.f;
        const float f0 = st0.y * sc, f1 = st1.y * sc;
#pragma unroll
        for (int j = 0; j < 9; j++) {
            const float* a = &acc[4 * (9 * p + j + ODD)];
            w[18 * p + 2 * j] = pack_bf16((a[0] - st0.x * cs[j].x) * f0, (a[1] - st0.x * cs[j].y) * f0);
            w[18 * p + 2 * j + 1] = pack_bf16((a[2] - st1.x * cs[j].x) * f1, (a[3] - st1.x * cs[j].y) * f1);
            sts32(addr[j] + p * 4 * BLK_BYTES, w[18 * p + 2 * j]);
            sts32(addr[j] + gs + p * 4 * BLK_BYTES, w[18 * p + 2 * j + 1]);
        }
        if (WFENCE) fence_async_smem();
        __syncwarp();
        if (lane == 0) mbar_arrive(bar_out + 8 * p);
        if (warp == 0 && lane == 0) TC(0, 23 + p);
    }
    if (ct < 2) return;
#pragma unroll
    for (int i = 0; i < 54; i++) vmax = absmax_bf16x2(vmax, w[i]);
    float m = fmaxf(fabsf(bf_lo(vmax)), fabsf(bf_hi(vmax)));
#pragma unroll
    for (int o = 16; o > 0; o >>= 1) m = fmaxf(m, __shfl_xor_sync(~0u, m, o));
    if (lane == 0) g_kmax[ct * 128 + rb * 8 + warp] = m;
}

__global__ void __launch_bounds__(384, 1)
qkv_kernel(const __grid_constant__ CUtensorMap tm_x, const __grid_constant__ CUtensorMap tm_w, const __nv_bfloat16* __restrict__ x) {
    extern __shared__ uint8_t smem_raw[];
    const int tid = threadIdx.x, warp = __shfl_sync(~0u, tid >> 5, 0), lane = tid & 31;
    pdl_launch();
    if (tid == 0) { TL(0, 0); TC(0, 0); }
    const uint32_t sb = (smem_u32(smem_raw) + 1023u) & ~1023u;
    const uint32_t bar_a = sb + A_OFF_MISC, bar_full = bar_a + 72, bar_empty = bar_full + 96, bar_xfree = bar_empty + 56;
    const uint32_t bar_dead = bar_xfree + 40, bar_out = bar_dead + 8;
    const uint32_t s_cs = sb + A_OFF_MISC + 512, s_st = s_cs + 1024, s_red = s_st + 1024;
    const int rb = blockIdx.x & 15, ct = blockIdx.x >> 4;
    const uint32_t rank = blockIdx.x & 1;
    const int col0 = 216 * ct - 8 * (ct & 1);
    const int krot = rb >> 1;

    if (lane == 0) {
        mbar_init(bar_a + 8 * warp, 1);
        const int es = warp >= 9 ? warp - 9 : warp + 3, a0 = (8 * krot) >> 5, a1 = (8 * krot + 36) >> 5;
        const uint32_t ecnt = 4 + (es == a0 || es == a0 + 1) + (es == a1 || es == a1 + 1);
        mbar_init(bar_a + 8 * (warp + 12), warp < 9 ? 1 : ecnt);
        if (warp < 10) mbar_init(bar_a + 8 * (warp + 24), warp < 4 ? ecnt : 2);
        if (warp >= 2 && warp < 5) mbar_init(bar_out + 8 * (warp - 2), 8);
        fence_mbar_init();
        if (warp == 0) {
            mbar_expect(bar_a, 16384);
            tma_2d(sb + x_slot(0), &tm_x, krot * 64, rb * 128, bar_a);
        }
        if (warp == 1) tma_prefetch_desc(&tm_w);
    }
    __syncwarp();
    cluster_sync();
    if (lane == 0) {
        if (warp < 4) {
            mbar_expect(bar_full + 8 * warp, A_STAGE_BYTES);
            tma_3d_mc(sb + warp * A_STAGE_BYTES + rank * 7168, &tm_w, col0, krot * 64 + warp * 32 + rank * 16, bar_full + 8 * warp);
        } else if (warp == 4) {
            mbar_expect(bar_a + 8, 16384);
            tma_2d(sb + x_slot(1), &tm_x, krot * 64 + 64, rb * 128, bar_a + 8);
        }
    }
    __syncwarp();

    if (warp == 8) {
        if (lane == 0) {
#pragma unroll 1
            for (int s = 4; s < 20; s++) {
                if (s < 7 ? !(s & 1) : (s > 10 && (s & 1))) {
                    const int kc = s < 7 ? s >> 1 : (s >> 1) - 1;
                    if (kc >= 4) mbar_wait_trap(bar_xfree + 8 * (kc - 4), 0);
                    mbar_expect(bar_a + 8 * kc, 16384);
                    tma_2d(sb + x_slot(kc), &tm_x, (krot + kc >= 9 ? krot + kc - 9 : krot + kc) * 64, rb * 128, bar_a + 8 * kc);
                }
                if (s < 18) {
                    const int slot = s >= A_STAGES ? s - A_STAGES : s;
                    if (s >= A_STAGES) mbar_wait_trap(bar_empty + 8 * slot, 0);
                    TC(0, 32 + s);
                    int k = krot * 64 + s * 32;
                    if (k >= DM) k -= DM;
                    mbar_expect(bar_full + 8 * slot, A_STAGE_BYTES);
                    tma_3d_mc(sb + slot * A_STAGE_BYTES + rank * 7168, &tm_w, col0, k + rank * 16, bar_full + 8 * slot);
                }
            }
        }
        __syncwarp();
        if (lane < 4) {
#pragma unroll 1
            for (int p = 0; p < 3; p++) {
                mbar_wait_trap(bar_out + 8 * p, 0);
                if (!WFENCE) fence_async_smem();
                bulk_store(g_qkv + (size_t)(ct * 12 + 4 * p + lane) * SLOT_BYTES + rb * BLK_BYTES, sb + A_OFF_STG + (4 * p + lane) * BLK_BYTES, BLK_BYTES);
                bulk_commit();
                if (lane == 0) TC(0, 26 + p);
            }
            if (lane == 0) TL(0, 4);
            bulk_wait_all();
            if (lane == 0) { TL(0, 5); TC(0, 29); }
        }
    } else if (warp > 8) {
        if (warp == 9) {
            const int u = (lane < 27 ? lane : 0) + (ct & 1), r0 = 8 * krot + 36 * rank;
            {
                uint4 v[36];
                uint32_t seen = 0;
                mbar_wait_trap(bar_full + 8 * (r0 >> 5), 0);
                mbar_wait_trap(bar_full + 8 * (r0 >> 5) + 8, 0);
#pragma unroll
                for (int k = 0; k < 36; k++) {
                    const int r = r0 + (k & ~3);
                    v[k] = lds128(sb + (r >> 4) * 7168 + ((r & 15) + (k & 3)) * 64 + (u >> 2) * 1024 + (((u & 3) ^ (((r + (k & 3)) >> 1) & 3)) << 4));
                    seen |= v[k].x;
                }
                sts32(s_red + lane * 4, seen);
                __syncwarp();
                if (lane < 4) mbar_arrive_cluster(mapa(bar_empty + 8 * ((r0 >> 5) + (lane >> 1)), lane & 1));
                float c0 = 0.f, c1 = 0.f;
#pragma unroll
                for (int j = 0; j < 4; j++) {
                    c0 *= 0.f; c1 *= 0.f;
#pragma unroll
                    for (int k = 0; k < 36; k++) {
                        const uint32_t w = j == 0 ? v[k].x : j == 1 ? v[k].y : j == 2 ? v[k].z : v[k].w;
                        c0 += bf_lo(w); c1 += bf_hi(w);
                    }
                    if (lane < 27) st_strong(&g_cs0[(ct * 16 + rb) * 216 + lane * 8 + j * 2], __float_as_uint(c0) | 1u, __float_as_uint(c1) | 1u);
                }
            }
            if (lane == 0) TL(0, 7);
            if (lane < 12 && blockIdx.x * 12 + lane < N_FLAG_C) g_flag_c[blockIdx.x * 12 + lane] = 0;
#pragma unroll 1
            for (uint32_t it = 0; flag_poll((const unsigned int*)&g_cs0[(ct * 16 + (lane & 15)) * 216 + 215], true, 1) != ~0u; it++)
                if (it > SPIN_LIMIT) __trap();
            if (lane < 27) {
                uint4 v[32];
#pragma unroll 1
                for (uint32_t it = 0;; it++) {
                    bool ok = true;
#pragma unroll
                    for (int i = 0; i < 32; i++) {
                        v[i] = ld_strong(&g_cs0[(ct * 16 + (i >> 1)) * 216 + lane * 8 + (i & 1) * 4]);
                        ok = ok && v[i].x && v[i].y && v[i].z && v[i].w;
                    }
                    if (ok) break;
                    if (it > SPIN_LIMIT) __trap();
                }
#pragma unroll
                for (int hh = 0; hh < 2; hh++) {
                    float a = 0.f, b = 0.f, c = 0.f, d = 0.f;
#pragma unroll
                    for (int i = hh; i < 32; i += 2) { a += __uint_as_float(v[i].x); b += __uint_as_float(v[i].y); c += __uint_as_float(v[i].z); d += __uint_as_float(v[i].w); }
                    sts128(s_cs + 32 * (ct & 1) + lane * 32 + hh * 16, __float_as_uint(a), __float_as_uint(b), __float_as_uint(c), __float_as_uint(d));
                }
            }
        } else {
            const int row = tid - 320, rl = row >> 2;
            if (XWAIT) mbar_wait_trap(bar_a, 0);
            const uint4* px = (const uint4*)(x + (size_t)(rb * 128 + ct * 16 + rl) * DM) + (lane & 3);
            uint4 v[18];
#pragma unroll
            for (int i = 0; i < 18; i++) v[i] = __ldg(px + 4 * i);
            float sum = 0.f, sq = 0.f, sq1 = 0.f;
#pragma unroll
            for (int i = 0; i < 18; i++) {
                sum += bf_lo(v[i].x); sum1 += bf_hi(v[i].x); sum += bf_lo(v[i].y); sum1 += bf_hi(v[i].y);
                sum += bf_lo(v[i].z); sum1 += bf_hi(v[i].z); sum += bf_lo(v[i].w); sum1 += bf_hi(v[i].w);
            }
            if (CHAINS == 2) sum += sum1;
            sum += __shfl_xor_sync(~0u, sum, 1); sum += __shfl_xor_sync(~0u, sum, 2);
            const float mean = sum * (1.f / DM);
#pragma unroll
            for (int i = 0; i < 18; i++) {
                const uint32_t w[4] = {v[i].x, v[i].y, v[i].z, v[i].w};
#pragma unroll
                for (int k = 0; k < 4; k++) { const float a = bf_lo(w[k]) - mean, b = bf_hi(w[k]) - mean; sq = fmaf(a, a, sq); SQ1 = fmaf(b, b, SQ1); }
            }
            if (CHAINS == 2) sq += sq1;
            sq += __shfl_xor_sync(~0u, sq, 1); sq += __shfl_xor_sync(~0u, sq, 2);
            if ((lane & 3) == 0) st_strong(&g_xstat[rb * 128 + ct * 16 + rl], __float_as_uint(mean) | 1u, __float_as_uint(1.f / sqrtf(sq * (1.f / DM) + LN_EPS)) | 1u);
            if (row == 0) TL(0, 8);
#pragma unroll 1
            for (uint32_t it = 0;; it++) {
                const uint4 w = ld_strong(&g_xstat[rb * 128 + row * 2]);
                if (w.x && w.y && w.z && w.w) { sts128(s_st + row * 16, w.x, w.y, w.z, w.w); break; }
                if (it > SPIN_LIMIT) __trap();
            }
            __syncwarp();
            if (row == 0) TL(0, 6);
            mbar_wait_trap(bar_dead, 0);
            const uint32_t sel0 = ((POLY_PATTERN >> (row >> 3)) & 1) ? 0x3F803F80u : 0u, sel1 = ((POLY_PATTERN >> ((row >> 3) + 8)) & 1) ? 0x3F803F80u : 0u;
#pragma unroll 1
            for (int p = 0; p < 3; p++) {
                const int kind = (ct * 3 + p) >> 3;
                const uint32_t gs = kind == 2 ? 384u : 128u;
                const uint32_t a = sb + A_OFF_STG + p * 4 * BLK_BYTES + (row & 7) * 16 + (row >> 3) * gs + (kind == 2 ? 256u : 4096u);
                const uint32_t w0 = kind == 0 ? 0x42FE47C0u : kind == 2 ? 0x00003F80u : sel0, w1 = kind == 1 ? sel1 : w0;
#pragma unroll
                for (int i = 0; i < 4; i++) {
                    sts32(a + i * BLK_BYTES + 4, w0); sts64f(a + i * BLK_BYTES + 8, 0.f, 0.f);
                    sts32(a + i * BLK_BYTES + 8 * gs + 4, w1); sts64f(a + i * BLK_BYTES + 8 * gs + 8, 0.f, 0.f);
                }
            }
            fence_async_smem();
        }
        __syncwarp();
        nbar_arrive(2, 352);
    } else {
        const int wg = warp >> 2;
        float acc[112];
#pragma unroll
        for (int i = 0; i < 112; i++) acc[i] = 0.f;
        const uint32_t a_lo = desc_addr(sb + wg * 8192) | (1u << 16);
        const uint32_t b_lo = desc_addr(sb) | ((1024 >> 4) << 16);
        const uint32_t rel = (tid & 127) == 0 ? bar_empty : mapa(bar_empty, rank ^ 1);
        const bool do_rel = (tid & 95) == 0;
        uint32_t addr[9];
        qkv_addr(addr, sb + A_OFF_STG, ct >= 6, warp, lane);
        fence_regs(addr);
#pragma unroll 1
        for (int s = 0; s < 18; s++) {
            const int slot = s >= A_STAGES ? s - A_STAGES : s;
            if (!(s & 1)) mbar_wait(bar_a + 4 * s, 0);
            if (tid == 0) TC(0, 64 + s);
            mbar_wait(bar_full + 8 * slot, s >= A_STAGES);
            if (tid == 0 && s == 0) TL(0, 1);
            if (tid == 0) TC(0, 1 + s);
            const uint32_t al = a_lo + (x_slot(s >> 1) >> 4) + (s & 1) * 4, bl = b_lo + slot * (A_STAGE_BYTES >> 4);
            wg_fence();
            mma_ss_n224(acc, al, HI_SW128, bl, HI_SW64, 1);
            mma_ss_n224(acc, al + 2, HI_SW128, bl + (7168 >> 4), HI_SW64, 1);
            wg_commit();
            wg_wait<1>();
            if (do_rel && s >= 1 && s <= 18 - A_STAGES) mbar_arrive_cluster(rel + 8 * (s - 1));
            if ((tid & 127) == 64) {
                if (s >= 2 && s <= 10 && !(s & 1)) mbar_arrive(bar_xfree + 4 * (s - 2));
                if (s == 12) mbar_arrive(bar_dead);
            }
        }
        wg_wait<0>();
        fence_regs(acc);
        if (tid == 0) { TL(0, 2); TC(0, 20); }
        nbar_sync(2, 352);
        if (tid == 0) { TL(0, 3); TC(0, 21); }
        const float2 st0 = lds64f(s_st + (warp * 16 + (lane >> 2)) * 8), st1 = lds64f(s_st + (warp * 16 + 8 + (lane >> 2)) * 8);
        if (ct & 1) qkv_epilogue<1>(acc, addr, sb + A_OFF_STG, s_cs, bar_out, st0, st1, ct, rb, warp, lane);
        else qkv_epilogue<0>(acc, addr, sb + A_OFF_STG, s_cs, bar_out, st0, st1, ct, rb, warp, lane);
    }
}

constexpr uint32_t B_OFF_Q = 2 * SLOT_BYTES, B_OFF_KMAX = B_OFF_Q + 4 * BLK_BYTES, B_OFF_BAR = B_OFF_KMAX + 1024;
constexpr uint32_t B_SMEM = B_OFF_BAR + 64;
constexpr uint32_t QK_LBO = (2048 >> 4) << 16, V_LBO = (384 >> 4) << 16, HI_NOSW = 128 >> 4;

__device__ __forceinline__ uint32_t exp_pair_poly(float a, float b, uint32_t c_or, uint32_t c_mul) {
    const uint32_t u = __byte_perm(__float_as_uint(a), __float_as_uint(b), 0x5410);
    uint32_t g, w, p, r;
    asm("lop3.b32 %0, %1, 0x007F007F, %2, 0xEA;" : "=r"(g) : "r"(u), "r"(c_or));
    asm("fma.rn.f16x2 %0, %1, %2, %3;" : "=r"(w) : "r"(g), "r"(c_mul), "r"(0xC40EC40Eu));
    asm("fma.rn.f16x2 %0, %1, %1, %2;" : "=r"(p) : "r"(w), "r"(0x47AE47AEu));
    asm("lop3.b32 %0, %1, %2, 0x007F007F, 0xD8;" : "=r"(r) : "r"(u), "r"(p));
    return r;
}
template <int JOFF>
__device__ __forceinline__ void exp_tile(const float (&s)[32], uint32_t (&p)[16], uint32_t c_or, uint32_t c_mul) {
#pragma unroll
    for (int j = 0; j < 8; j++) {
        if ((POLY_PATTERN >> (j + JOFF)) & 1) {
            p[2 * j] = exp_pair_poly(s[4 * j], s[4 * j + 1], c_or, c_mul);
            p[2 * j + 1] = exp_pair_poly(s[4 * j + 2], s[4 * j + 3], c_or, c_mul);
        } else {
            p[2 * j] = pack_bf16(ex2(s[4 * j]), ex2(s[4 * j + 1]));
            p[2 * j + 1] = pack_bf16(ex2(s[4 * j + 2]), ex2(s[4 * j + 3]));
        }
    }
}
__device__ __forceinline__ void qk_tile(float (&s)[32], const uint32_t (&q)[8], uint64_t k) {
    mma_qk_first(s, q[0], q[1], q[2], q[3], k + QK_LBO);
    mma_qk_second(s, q[4], q[5], q[6], q[7], k + 256);
}
__device__ __forceinline__ void pv_tile(float (&o)[12], const uint32_t (&p)[16], uint64_t v) {
#pragma unroll
    for (int kk = 0; kk < 4; kk++) mma_pv(o, p[4 * kk], p[4 * kk + 1], p[4 * kk + 2], p[4 * kk + 3], v + kk * 48);
}
__device__ __forceinline__ void load_q(uint32_t (&q)[8], uint32_t sq) {
    q[0] = lds32(sq); q[1] = lds32(sq + 128); q[2] = lds32(sq + 2048); q[3] = lds32(sq + 2176);
    q[4] = lds32(sq + 4096); q[5] = lds32(sq + 4224); q[6] = lds32((sq + 4096) | 12); q[7] = lds32((sq + 4224) | 12);
}
__device__ __forceinline__ float q_l1(const uint32_t (&q)[8], int lane) {
    const bool first = (lane & 3) == 0;
    float n0 = fabsf(bf_lo(q[0])) + fabsf(bf_hi(q[0])) + fabsf(bf_lo(q[2])) + fabsf(bf_hi(q[2])) + (first ? fabsf(bf_lo(q[4])) + fabsf(bf_hi(q[4])) : 0.f);
    float n1 = fabsf(bf_lo(q[1])) + fabsf(bf_hi(q[1])) + fabsf(bf_lo(q[3])) + fabsf(bf_hi(q[3])) + (first ? fabsf(bf_lo(q[5])) + fabsf(bf_hi(q[5])) : 0.f);
    n0 += __shfl_xor_sync(~0u, n0, 1); n1 += __shfl_xor_sync(~0u, n1, 1);
    n0 += __shfl_xor_sync(~0u, n0, 2); n1 += __shfl_xor_sync(~0u, n1, 2);
    return n0 > n1 || n0 != n0 ? n0 : n1;
}
__device__ __forceinline__ void stage_attn(const float (&o)[12], uint32_t stg, int h, int tid) {
    const int lane = tid & 31;
    const float r0 = __fdividef(1.f, __shfl_sync(~0u, o[8], (lane & ~3) | 1)), r1 = __fdividef(1.f, __shfl_sync(~0u, o[10], (lane & ~3) | 1));
    const uint32_t a = stg + ((tid >> 6) & 1) * 2048 + ((tid >> 5) & 1) * 512 + lane * 8;
    sts64f(a, __uint_as_float(pack_bf16(o[0] * r0, o[1] * r0)), __uint_as_float(pack_bf16(o[4] * r0, o[5] * r0)));
    sts64f(a + 256, __uint_as_float(pack_bf16(o[2] * r1, o[3] * r1)), __uint_as_float(pack_bf16(o[6] * r1, o[7] * r1)));
    if ((lane & 3) == 0) {
        const uint32_t b = ((tid >> 5) & 3) * 64 + (h & 3) * 32 + lane;
        sts32(stg + 4096 + (b & 255), pack_bf16(o[8] * r0, o[9] * r0));
        sts32(stg + 4096 + ((b + 32) & 255), pack_bf16(o[10] * r1, o[11] * r1));
    }
}
__device__ __forceinline__ bool wg_any(bool pred, uint32_t id) {
    uint32_t r;
    asm volatile("{\n.reg .pred p, q;\nsetp.ne.u32 p, %1, 0;\nbar.red.or.pred q, %2, 128, p;\nselp.u32 %0, 1, 0, q;\n}\n" : "=r"(r) : "r"((uint32_t)pred), "r"(id) : "memory");
    return __any_sync(~0u, r);
}
__device__ __forceinline__ void attn_safe_block(uint64_t k0, uint32_t (&q)[8], float (&o)[12]) {
    if (threadIdx.x & 3) { q[4] = 0; q[5] = 0; }
    float s[32], m0 = -INFINITY, m1 = -INFINITY;
    uint32_t p[16];
#pragma unroll
    for (int i = 0; i < 12; i++) o[i] = 0.f;
#pragma unroll 1
    for (int i = 0; i < 32; i++) {
        wg_fence();
        qk_tile(s, q, k0 + (i >> 1) * 384 + (i & 1) * 64);
        wg_commit();
        wg_wait<0>();
        fence_regs(s);
        float n0 = m0, n1 = m1;
#pragma unroll
        for (int j = 0; j < 8; j++) { n0 = fmaxf(n0, fmaxf(s[4 * j], s[4 * j + 1])); n1 = fmaxf(n1, fmaxf(s[4 * j + 2], s[4 * j + 3])); }
        n0 = fmaxf(n0, __shfl_xor_sync(~0u, n0, 1)); n0 = fmaxf(n0, __shfl_xor_sync(~0u, n0, 2));
        n1 = fmaxf(n1, __shfl_xor_sync(~0u, n1, 1)); n1 = fmaxf(n1, __shfl_xor_sync(~0u, n1, 2));
        const float c0 = ex2(m0 - n0), c1 = ex2(m1 - n1);
        m0 = n0; m1 = n1;
#pragma unroll
        for (int j = 0; j < 3; j++) { o[4 * j] *= c0; o[4 * j + 1] *= c0; o[4 * j + 2] *= c1; o[4 * j + 3] *= c1; }
#pragma unroll
        for (int j = 0; j < 8; j++) {
            p[2 * j] = pack_bf16(ex2(s[4 * j] - m0), ex2(s[4 * j + 1] - m0));
            p[2 * j + 1] = pack_bf16(ex2(s[4 * j + 2] - m1), ex2(s[4 * j + 3] - m1));
        }
        fence_regs(o);
        wg_fence();
        pv_tile(o, p, k0 + (SLOT_BYTES >> 4) + V_LBO + i * 192);
        wg_commit();
        wg_wait<0>();
        fence_regs(o);
    }
}

__global__ void __launch_bounds__(512, 1)
attn_kernel(const __grid_constant__ CUtensorMap tm_wo, const __grid_constant__ CUtensorMap tm_wo2, const __grid_constant__ CUtensorMap tm_ast,
            const __nv_bfloat16* __restrict__ w1, const __nv_bfloat16* __restrict__ w2) {
    extern __shared__ __align__(128) uint8_t smem_raw[];
    const int tid = threadIdx.x, lane = tid & 31;
    if (tid == 0) TL(1, 0);
    const uint32_t sk = smem_u32(smem_raw), sv = sk + SLOT_BYTES, bar = sk + B_OFF_BAR;
    if (blockIdx.x < 4) {
        pdl_launch();
        if (tid == 480) {
            mbar_init(bar, 1);
            fence_mbar_init();
            fence_async_smem();
            mbar_expect(bar, 2 * 82944);
#pragma unroll 1
            for (int i = 0; i < 4; i++)
                asm volatile("cp.async.bulk.tensor.4d.shared::cluster.global.mbarrier::complete_tx::bytes [%0], [%1, {%3, %4, %4, %5}], [%2];"
                             :: "r"(sk + 16384 + (i >> 1) * 82944 + (i & 1) * 36864), "l"(&tm_wo), "r"(bar), "r"((blockIdx.x * 2 + (i >> 1)) * 72), "r"(0), "r"((i & 1) * 16) : "memory");
#pragma unroll 1
            for (int i = 0; i < 2; i++)
                asm volatile("cp.async.bulk.tensor.5d.shared::cluster.global.mbarrier::complete_tx::bytes [%0], [%1, {%3, %4, %4, %4, %4}], [%2];"
                             :: "r"(sk + 16384 + i * 82944 + 73728), "l"(&tm_wo2), "r"(bar), "r"((blockIdx.x * 2 + i) * 72), "r"(0) : "memory");
            mbar_wait(bar, 0);
            bulk_store(g_wo_img + blockIdx.x * 2 * 82944, sk + 16384, 2 * 82944);
            bulk_commit();
            bulk_wait_all();
#pragma unroll 1
            for (int i = 0; i < 32 * HELPER_PF; i++) l2_prefetch((const uint8_t*)w2 + (size_t)(blockIdx.x * 32 + i) * 41472, 41472);
            pdl_wait();
            flag_add(&g_flag_c[FLAG_WO + blockIdx.x * 2]);
            flag_add(&g_flag_c[FLAG_WO + blockIdx.x * 2 + 1]);
        }
        float* red = (float*)smem_raw;
        const int cg = tid % 144, part = tid / 144;
        float c[8] = {0.f, 0.f, 0.f, 0.f, 0.f, 0.f, 0.f, 0.f};
        if (part < 3) {
            const uint4* pw = (const uint4*)(w1 + (size_t)part * 192 * FF + blockIdx.x * 1152) + cg;
#pragma unroll 16
            for (int k = 0; k < 192; k++) {
                const uint4 v = __ldg(pw + (size_t)k * (FF / 8));
                c[0] += bf_lo(v.x); c[1] += bf_hi(v.x); c[2] += bf_lo(v.y); c[3] += bf_hi(v.y);
                c[4] += bf_lo(v.z); c[5] += bf_hi(v.z); c[6] += bf_lo(v.w); c[7] += bf_hi(v.w);
            }
#pragma unroll
            for (int k = 0; k < 8; k++) red[part * 1152 + cg * 8 + k] = c[k];
        }
        __syncthreads();
        for (int i = tid; i < 144 * 8; i += 512) {
            const int core = i >> 3, k = i & 7;
            uint32_t w[4] = {0u, 0u, 0u, 0u};
            if (k < 3) {
#pragma unroll
                for (int j = 0; j < 4; j++) {
                    const int c0 = core * 8 + 2 * j;
                    const float a = -(red[c0] + red[1152 + c0] + red[2304 + c0]), b = -(red[c0 + 1] + red[1153 + c0] + red[2305 + c0]);
                    const uint32_t hi = pack_bf16(a, b);
                    w[j] = k == 1 ? pack_bf16(a - bf_lo(hi), b - bf_hi(hi)) : hi;
                }
            }
            ((uint4*)g_cs1)[blockIdx.x * 1152 + i] = make_uint4(w[0], w[1], w[2], w[3]);
        }
        if (tid == 0) TL(1, 5);
        return;
    }
    const int h = (blockIdx.x - 4) >> 2, qt = blockIdx.x & 3;
    if (lane == 0 && tid < 96) {
        mbar_init(bar + (tid >> 2), 1);
        fence_mbar_init();
    }
    if (tid == 192) tma_prefetch_desc(&tm_ast);
    if (tid == 160) { sts32(bar + 40, 0x48004800u); sts32(bar + 44, 0x38A038A0u); }
    __syncthreads();
    const uint32_t c_or = lds32(bar + 40), c_mul = lds32(bar + 44);
    {
        const int w = tid >> 7;
        const uint8_t* src = g_qkv + (size_t)((w & 1) * (16 + 16 * w) + h) * SLOT_BYTES + ((w & 1) ? 0 : (qt * 4 + w) * BLK_BYTES);
        const uint32_t dst = (w & 1) ? sk + (w >> 1) * SLOT_BYTES : sk + B_OFF_Q + w * BLK_BYTES;
        uint32_t bytes = (w & 1) ? BLK_BYTES : 2 * BLK_BYTES;
        if (tid == 0) mbar_expect(bar, 6 * BLK_BYTES);
        asm volatile("" : "+l"(src), "+r"(bytes) :: "memory");
        pdl_wait();
        if ((tid & 127) == 0) bulk_load(dst, src, bytes, bar);
        pdl_launch();
        if (tid < 8) ((uint4*)g_xstat)[(blockIdx.x - 4) * 8 + tid] = make_uint4(0, 0, 0, 0);
        else if (tid < 62) ((uint4*)g_cs0)[(blockIdx.x - 4) * 54 + tid - 8] = make_uint4(0, 0, 0, 0);
    }
    if (tid == 0) { TL(1, 1); TC(1, 0);
    }
    const uint8_t* gk = g_qkv + (size_t)(32 + h) * SLOT_BYTES;
    auto load_kv = [&](uint32_t off, uint32_t bytes, uint32_t b) {
        bulk_load(sk + off, gk + off, bytes, b);
        bulk_load(sv + off, gk + 32 * SLOT_BYTES + off, bytes, b);
    };
    const uint64_t k0 = desc_addr(sk) | ((uint64_t)HI_NOSW << 32);
    const uint32_t sq = sk + B_OFF_Q + (tid >> 8) * BLK_BYTES + ((tid >> 5) & 7) * 256 + lane * 4;
    float oa[12], ob[12];
#pragma unroll
    for (int i = 0; i < 12; i++) { oa[i] = 0.f; ob[i] = 0.f; }
    mbar_wait(bar, 0);
    uint32_t qa[8], qb[8];
    load_q(qa, sq);
    load_q(qb, sq + 2 * BLK_BYTES);
    fence_regs(oa); fence_regs(ob); fence_regs(qa); fence_regs(qb);
    {
        float s[32]; uint32_t p[16];
        uint64_t k = k0;
#pragma unroll 1
        for (int seg = 0; seg < 3; seg++) {
            mbar_wait(bar + 8 * seg, 0);
            if (seg == 0 && tid == 256) { mbar_expect(bar + 8, 6 * BLK_BYTES); load_kv(BLK_BYTES, 3 * BLK_BYTES, bar + 8); }
            if (seg == 1 && tid == 384) {
                mbar_expect(bar + 16, 24 * BLK_BYTES + 1024);
                load_kv(4 * BLK_BYTES, 12 * BLK_BYTES, bar + 16);
                bulk_load(sk + B_OFF_KMAX, g_kmax + ((32 + h) / 12) * 128, 512, bar + 16);
                bulk_load(sk + B_OFF_KMAX + 512, g_kmax + ((64 + h) / 12) * 128, 512, bar + 16);
            }
            __syncwarp();
            if (tid == 0 && seg == 0) TL(1, 2);
            if ((tid & 127) == 0) TC(1, 16 + (tid >> 7) * 16 + seg);
            const int nblk = seg == 0 ? 1 : seg == 1 ? 3 : 12;
#pragma unroll 1
            for (int b = 0; b < nblk; b++, k += 384) {
                const uint64_t v = k + (SLOT_BYTES >> 4) + V_LBO;
                wg_fence();
                qk_tile(s, qa, k);
                wg_commit();
                wg_wait<0>();
                fence_regs(s); fence_regs(p);
                exp_tile<0>(s, p, c_or, c_mul);
                wg_fence();
                pv_tile(oa, p, v);
                qk_tile(s, qb, k);
                wg_commit();
                wg_wait<0>();
                fence_regs(s); fence_regs(p);
                exp_tile<0>(s, p, c_or, c_mul);
                wg_fence();
                pv_tile(ob, p, v);
                qk_tile(s, qa, k + 64);
                wg_commit();
                wg_wait<0>();
                fence_regs(s); fence_regs(p);
                exp_tile<8>(s, p, c_or, c_mul);
                wg_fence();
                pv_tile(oa, p, v + 192);
                qk_tile(s, qb, k + 64);
                wg_commit();
                wg_wait<0>();
                fence_regs(s); fence_regs(p);
                exp_tile<8>(s, p, c_or, c_mul);
                wg_fence();
                pv_tile(ob, p, v + 192);
                wg_commit();
            }
        }
    }
    if ((tid & 127) == 0) TC(1, 16 + (tid >> 7) * 16 + 5);
    const uint4 km = lds128(sk + B_OFF_KMAX + lane * 16), vm = lds128(sk + B_OFF_KMAX + 512 + lane * 16);
    const float kmax = __uint_as_float(__reduce_max_sync(~0u, max(max(km.x, km.y), max(km.z, km.w))));
    const float vmax = __uint_as_float(__reduce_max_sync(~0u, max(max(vm.x, vm.y), max(vm.z, vm.w))));
    const bool unsafe = wg_any(!(fmaxf(q_l1(qa, lane), q_l1(qb, lane)) * kmax <= 100.f && vmax <= 32768.f), 1 + (tid >> 7));
    if ((tid & 127) == 0) TC(1, 16 + (tid >> 7) * 16 + 6);
    wg_wait<0>();
    fence_regs(oa); fence_regs(ob);
    if ((tid & 127) == 0) TC(1, 16 + (tid >> 7) * 16 + 7);
    const uint32_t stg = sk + B_OFF_Q + (tid >> 8) * BLK_BYTES + ((tid >> 7) & 1) * 1024;
    if (!unsafe) {
        stage_attn(oa, stg, h, tid);
        stage_attn(ob, stg + 2 * BLK_BYTES, h, tid);
    } else {
#pragma unroll 1
        for (int u = 0; u < 2; u++) {
            load_q(qa, sq + u * 2 * BLK_BYTES);
            attn_safe_block(k0, qa, oa);
            stage_attn(oa, stg + u * 2 * BLK_BYTES, h, tid);
        }
    }
    fence_async_smem();
    nbar_sync(1 + (tid >> 7), 128);
    if (lane == 0) {
        const int w = (tid >> 5) & 3, row = qt * 512 + (w >> 1) * 256 + (tid >> 7) * 64;
        tma_store_2d(&tm_ast, stg + (w >> 1) * 2 * BLK_BYTES + (w & 1) * 2048, h * 16, row + (w & 1) * 32);
        if (!(w & 1)) bulk_store(g_rem + (row >> 7) * 4096 + h * 128 + (row & 127), stg + (w >> 1) * 2 * BLK_BYTES + 4096, 256);
        bulk_commit();
        bulk_wait_all();
    }
    if ((tid & 127) == 0) { TL(1, 5 + (tid >> 7)); TC(1, 1 + (tid >> 7)); }
}

constexpr uint32_t C_HALF = 73728;
constexpr uint32_t C_OFF_W = 147456, C_SLOT = 6144;
constexpr uint32_t C_OFF_CS = C_OFF_W + 12 * C_SLOT;
constexpr uint32_t C_OFF_BAR = C_OFF_W + 82944;
constexpr uint32_t C_SMEM = C_OFF_BAR + 1024 + 1024;

struct RowStat { float mean, rstd; };
__device__ __forceinline__ RowStat combine_hstat(float2 u, float2 v) {
    float sum = u.x + v.x;
    sum += __shfl_xor_sync(~0u, sum, 1); sum += __shfl_xor_sync(~0u, sum, 2);
    const float mean = sum * (1.f / DM);
    const float d0 = u.x * (1.f / 72) - mean, d1 = v.x * (1.f / 72) - mean;
    float m2 = u.y + v.y + 72.f * (d0 * d0 + d1 * d1);
    m2 += __shfl_xor_sync(~0u, m2, 1); m2 += __shfl_xor_sync(~0u, m2, 2);
    return {mean, 1.f / sqrtf(m2 * (1.f / DM) + LN_EPS)};
}
__device__ __forceinline__ uint32_t mean_frag(float m, int t) {
    const uint32_t hi = pack_bf16(m, m);
    return t == 0 ? hi : t == 1 ? pack_bf16(m - bf_lo(hi), 0.f) : 0u;
}
__device__ __forceinline__ void add_partial(float (&acc)[32], uint32_t src) {
#pragma unroll
    for (int i = 0; i < 4; i++) {
        const uint4 v = lds128(src + i * 512);
        acc[8 * i] += bf_lo(v.x); acc[8 * i + 1] += bf_hi(v.x); acc[8 * i + 2] += bf_lo(v.y); acc[8 * i + 3] += bf_hi(v.y);
        acc[8 * i + 4] += bf_lo(v.z); acc[8 * i + 5] += bf_hi(v.z); acc[8 * i + 6] += bf_lo(v.w); acc[8 * i + 7] += bf_hi(v.w);
    }
}

__global__ void __launch_bounds__(384, 1)
ffn_kernel(const __grid_constant__ CUtensorMap tm_attn, const __grid_constant__ CUtensorMap tm_w1, const __grid_constant__ CUtensorMap tm_w2,
           const __grid_constant__ CUtensorMap tm_out, const __nv_bfloat16* __restrict__ x, __nv_bfloat16* __restrict__ out) {
    extern __shared__ uint8_t smem_raw[];
    const int tid = threadIdx.x, warp = __shfl_sync(~0u, tid >> 5, 0), lane = tid & 31;
    const uint32_t sb = (smem_u32(smem_raw) + 1023u) & ~1023u;
    const uint32_t bar_a = sb + C_OFF_BAR, bar_full = bar_a + 72, bar_wo = bar_full + 96, bar_cs = bar_wo + 8, bar_recv = bar_cs + 8;
    const uint32_t bar_hst = bar_recv + 16, bar_tfree = bar_hst + 8, bar_h = bar_tfree + 8, bar_g1 = bar_h + 64, bar_afree = bar_g1 + 8;
    const uint32_t bar_empty = bar_afree + 8, bar_pub = bar_empty + 96, bar_hpub = bar_pub + 64;
    const int rb = blockIdx.x & 15, e = blockIdx.x >> 4;
    const uint32_t rank = blockIdx.x & 1;
    const int wrb = blockIdx.x >> 3, wsl = blockIdx.x & 7;
    if (tid == 0) { TL(2, 0); TC(2, 0); }

    if (lane == 0) {
        const uint32_t wo_ready = warp == 9 ? flag_read(&g_flag_c[FLAG_WO + wsl]) : 0;
#pragma unroll
        for (int i = 0; i < 5; i++) {
            const int b = warp + 12 * i;
            if (b < 59) mbar_init(bar_a + 8 * b, b < 27 ? 1 : b < 37 ? 2 : b < 49 ? 4 : 8);
        }
        fence_mbar_init();
        mbar_expect(bar_a + 8 * (warp < 9 ? warp + 12 : warp), C_SLOT);
        if (warp == 9) {
            if (!wo_ready) for (uint32_t i = 0; i < SPIN_LIMIT && !flag_read(&g_flag_c[FLAG_WO + wsl]); i++) ;
            flag_acquire();
            mbar_expect(bar_wo, 82944);
#pragma unroll 1
            for (int i = 0; i < 3; i++) bulk_load(sb + C_OFF_W + i * 27648, g_wo_img + wsl * 82944 + i * 27648, 27648, bar_wo);
        }
    }
    __syncwarp();
    if (tid == 320) { tma_prefetch_desc(&tm_attn); tma_prefetch_desc(&tm_w1); tma_prefetch_desc(&tm_w2); tma_prefetch_desc(&tm_out); }
    cluster_sync();

    if (warp >= 8) {
        asm volatile("setmaxnreg.dec.sync.aligned.u32 40;");
        if (warp == 8) {
            if (lane == 0) {
                pdl_wait();
                TL(2, 1); TC(2, 1);
#pragma unroll 1
                for (int kc = 0; kc < 8; kc++) {
                    mbar_expect(bar_a + 8 * kc, 16384);
                    tma_2d_mc(sb + kc * 16384 + rank * 8192, &tm_attn, kc * 64, wrb * 128 + rank * 64, bar_a + 8 * kc);
                    if (kc == 0) {
                        TC(2, 8);
                        mbar_expect(bar_a + 64, 16384);
                        asm volatile("cp.async.bulk.shared::cluster.global.mbarrier::complete_tx::bytes.multicast::cluster [%0], [%1], %2, [%3], %4;"
                                     :: "r"(sb + 8 * 16384 + rank * 8192), "l"(g_rem + wrb * 4096 + rank * 2048), "r"(8192), "r"(bar_a + 64), "h"((uint16_t)3) : "memory");
                    }
                    if (kc == 7) TC(2, 14);
                }
                uint32_t ph = 0;
#pragma unroll 1
                for (int rnd = 0; rnd < 18; rnd++) {
                    const int pass = rnd / 3, p = rnd - 9;
                    const int c0 = rnd < 9 ? e * 576 + pass * 192 : (p == 0 ? 8 : (e + p) & 7) * 64;
                    const int r0 = rnd < 9 ? (rnd - pass * 3) * 192 : e * 576;
                    if (W2PF && rb < 12 && p + W2PF >= 0 && p + W2PF < 9)
                        asm volatile("cp.async.bulk.prefetch.tensor.2d.L2.global [%0, {%1, %2}];"
                                     :: "l"(&tm_w2), "r"((p + W2PF == 0 ? 8 : (e + p + W2PF) & 7) * 64), "r"(e * 576 + rb * 48) : "memory");
#pragma unroll 1
                    for (int slot = rank; slot < 12; slot += 2) {
                        mbar_wait_trap(bar_empty + 8 * slot, ph);
                        TC(2, 128 + rnd * 6 + (slot >> 1));
                        if (rnd < 9) tma_3d_mc(sb + C_OFF_W + slot * C_SLOT, &tm_w1, c0, r0 + slot * 16, bar_full + 8 * slot);
                        else tma_2d_mc(sb + C_OFF_W + slot * C_SLOT, &tm_w2, c0, r0 + slot * 48, bar_full + 8 * slot);
                    }
                    ph ^= 1;
                }
            }
        } else if (warp == 11) {
            if (lane == 0) {
                mbar_wait_trap(bar_hpub, 0);
                flag_add(&g_flag_c[FLAG_H + wrb * 8 + wsl]);
                TC(2, 4);
                mbar_expect(bar_cs, 9216);
                bulk_load(sb + C_OFF_CS, g_cs1 + e * 9216, 9216, bar_cs);
                mbar_wait_trap(bar_hpub + 8, 0);
                flag_add(&g_flag_c[FLAG_HST + wrb]);
                flag_wait(&g_flag_c[FLAG_HST + rb], 8);
                mbar_arrive(bar_hst);
            }
            __syncwarp();
            mbar_wait_trap(bar_g1, 0);
#pragma unroll 1
            for (int i = 0; i < 4; i++) {
                const uint4 v = lds128(sb + (e >> 2) * C_HALF + (64 + 2 * i + (lane >> 4)) * 1024 + (e & 3) * 256 + (lane & 15) * 16);
                sts128(sb + C_OFF_CS + i * 512 + lane * 16, v.x, v.y, v.z, v.w);
            }
            __syncwarp();
            const int r = lane >> 2, t = lane & 3, row = rb * 128 + e * 16 + r;
            const float rs0 = combine_hstat(__ldcg(&g_hstat[2 * t * SEQ + row]), __ldcg(&g_hstat[(2 * t + 1) * SEQ + row])).rstd;
            const float rs1 = combine_hstat(__ldcg(&g_hstat[2 * t * SEQ + row + 8]), __ldcg(&g_hstat[(2 * t + 1) * SEQ + row + 8])).rstd;
            const uint32_t tmp = sb + ((e + 2) & 7) * 8192;
            if (lane < 8) flag_wait(&g_flag_c[FLAG_PART + (rb * 9 + 8) * 8 + lane], 1);
            __syncwarp();
            if (lane == 0) {
                TC(2, 124);
                mbar_expect(bar_cs, 16384);
#pragma unroll 1
                for (int c = 0; c < 8; c++)
                    bulk_load(tmp + (c >> 2) * C_HALF + (c & 3) * 2048, g_part + (size_t)((rb * 9 + 8) * 8 + c) * 16384 + e * 2048, 2048, bar_cs);
            }
            if (lane == 0) TC(2, 125);
            mbar_wait_trap(bar_cs, 1);
            if (lane == 0) TC(2, 126);
#pragma unroll 1
            for (int i = 0; i < 8; i++) {
                const uint32_t h0 = lds32(sb + C_OFF_CS + i * 256 + lane * 4), h1 = lds32(sb + C_OFF_CS + i * 256 + 128 + lane * 4);
                float a0 = 0.f, a1 = 0.f, a2 = 0.f, a3 = 0.f;
#pragma unroll
                for (int c = 0; c < 8; c++) {
                    const float2 v = lds64f(tmp + (c >> 2) * C_HALF + (c & 3) * 2048 + (i >> 1) * 512 + lane * 16 + (i & 1) * 8);
                    a0 += bf_lo(__float_as_uint(v.x)); a1 += bf_hi(__float_as_uint(v.x)); a2 += bf_lo(__float_as_uint(v.y)); a3 += bf_hi(__float_as_uint(v.y));
                }
                uint32_t* po = (uint32_t*)out + ((size_t)row * DM + 512 + 8 * i) / 2 + t;
                po[0] = pack_bf16(bf_lo(h0) + rs0 * a0, bf_hi(h0) + rs0 * a1);
                po[4 * DM] = pack_bf16(bf_lo(h1) + rs1 * a2, bf_hi(h1) + rs1 * a3);
            }
            fence_async_smem();
            __syncwarp();
            if (lane == 0) { TC(2, 127); mbar_arrive(bar_tfree); }
        } else {
            const int w = warp - 9;
            mbar_wait_trap(bar_afree, 0);
#pragma unroll 1
            for (uint32_t sl = 0, it = 0; sl < 8; it++) {
                const uint32_t m = flag_poll(&g_flag_c[FLAG_H + rb * 8 + (lane & 7)], lane < 8, 1);
#pragma unroll 1
                for (; sl < 8 && ((m >> sl) & 1); sl++) {
                    if (lane == 0) {
                        if (sl == 0 && w == 0) TC(2, 5);
                        if (sl >= 2) mbar_wait_trap(bar_h + 8 * (sl - 2), 0);
                        flag_acquire();
                        mbar_expect(bar_h + 8 * sl, 9216);
                        bulk_load(sb + w * C_HALF + sl * 9216, g_h + rb * 147456 + w * C_HALF + sl * 9216, 9216, bar_h + 8 * sl);
                    }
                    __syncwarp();
                }
                if (it > SPIN_LIMIT) __trap();
            }
            if (w == 0) {
                if (lane == 0) {
                    TL(2, 4); TC(2, 7);
#pragma unroll 1
                    for (int p = 0; p < 8; p++) {
                        mbar_wait_trap(bar_pub + 8 * p, 0);
                        flag_add(&g_flag_c[FLAG_PART + (rb * 9 + (p == 0 ? 8 : (e + p) & 7)) * 8 + e]);
                    }
                }
            } else {
                mbar_wait_trap(bar_g1, 0);
                if (lane == 0) { mbar_expect(bar_recv, 5 * 16384); mbar_expect(bar_wo, 16384); mbar_expect(bar_recv + 8, 16384); }
#pragma unroll 1
                for (uint32_t p = 1, it = 0; p < 8; it++) {
                    const uint32_t m = flag_poll(&g_flag_c[FLAG_PART + (rb * 9 + e) * 8 + ((e - lane) & 7)], lane < 8, 1);
#pragma unroll 1
                    for (; p < 8 && ((m >> p) & 1); p++) {
                        if (lane == 0) {
                            const int c = (e - p) & 7;
                            const uint8_t* src = g_part + (size_t)((rb * 9 + e) * 8 + c) * 16384;
                            TC(2, 248 + p);
                            if (p == 6) mbar_wait_trap(bar_tfree, 0);
                            flag_acquire();
                            const uint32_t dst = sb + (p == 7 ? 8 : c) * 8192;
                            const uint32_t b = p < 6 ? bar_recv : p == 6 ? bar_wo : bar_recv + 8;
                            bulk_load(dst, src, 8192, b);
                            bulk_load(dst + C_HALF, src + 8192, 8192, b);
                        }
                        __syncwarp();
                    }
                    if (it > SPIN_LIMIT) __trap();
                }
            }
        }
    } else {
        asm volatile("setmaxnreg.inc.sync.aligned.u32 232;");
        const int wg = warp >> 2, t = lane & 3, r = lane >> 2;
        const uint32_t rel = mapa(bar_empty, warp & 1);
        const bool rel_even = (tid & 127) == 0, rel_odd = (tid & 127) == 32, arm = tid == 64;
        {
            const uint32_t* px = (const uint32_t*)(x + (size_t)(wrb * 128 + warp * 16 + r) * DM + wsl * 72) + t;
            uint32_t xr[18];
#pragma unroll
            for (int j = 0; j < 9; j++) { xr[2 * j] = __ldg(px + 4 * j); xr[2 * j + 1] = __ldg(px + 8 * (DM / 2) + 4 * j); }
            float acc[36];
#pragma unroll
            for (int i = 0; i < 36; i++) acc[i] = 0.f;
            fence_regs(acc);
            const uint32_t a_lo = desc_addr(sb + wg * 8192) | (1u << 16);
            const uint32_t b_lo = desc_addr(sb + C_OFF_W) | ((128 >> 4) << 16);
            mbar_wait(bar_wo, 0);
            if (tid == 0) TC(2, 6);
            auto wo_chunks = [&](int k0, int k1) {
#pragma unroll 1
                for (int kc = k0; kc < k1; kc++) {
                    mbar_wait(bar_a + 8 * kc, 0);
                    if (tid == 0) TC(2, 240 + kc);
                    wg_fence();
#pragma unroll
                    for (int j = 0; j < 4; j++) mma_ss_n72(acc, a_lo + kc * 1024 + j * 2, HI_SW128, b_lo + (kc * 4 + j) * 144, 256 >> 4, 1);
                    wg_commit();
                }
            };
            wo_chunks(0, REM_AT);
            mbar_wait(bar_a + 64, 0);
            if (tid == 0) TC(2, 15);
            uint32_t ar[16];
#pragma unroll
            for (int i = 0; i < 16; i++) ar[i] = lds32(sb + 8 * 16384 + ((i >> 1) * 4 + t) * 512 + wg * 256 + (((warp & 3) * 16 + (i & 1) * 8 + t * 8 + r) & 63) * 4);
            wg_fence();
#pragma unroll
            for (int j = 0; j < 4; j++) mma_rs_n72(acc, ar[4 * j], ar[4 * j + 1], ar[4 * j + 2], ar[4 * j + 3], b_lo + (32 + j) * 144, 256 >> 4);
            wg_commit();
            wo_chunks(REM_AT, 8);
            wg_wait<0>();
            fence_regs(acc);
            if (tid == 0) { TL(2, 2); TC(2, 2); }
            if (rel_even || rel_odd) {
#pragma unroll
                for (int i = 0; i < 6; i++) mbar_arrive_cluster(rel + 8 * (warp & 1) + 16 * i);
            }
            if (rel_even) mbar_arrive(bar_afree);
            uint32_t hw[18];
            uint32_t* ph = (uint32_t*)(g_h + wrb * 147456 + wg * C_HALF + wsl * 9216 + (warp & 3) * 256) + lane;
#pragma unroll
            for (int j = 0; j < 9; j++) {
                hw[2 * j] = pack_bf16(acc[4 * j] + bf_lo(xr[2 * j]), acc[4 * j + 1] + bf_hi(xr[2 * j]));
                hw[2 * j + 1] = pack_bf16(acc[4 * j + 2] + bf_lo(xr[2 * j + 1]), acc[4 * j + 3] + bf_hi(xr[2 * j + 1]));
                ph[256 * j] = hw[2 * j]; ph[256 * j + 32] = hw[2 * j + 1];
            }
            __syncwarp();
            if (lane == 0) mbar_arrive(bar_hpub);
            if (tid == 0) { TL(2, 3); TC(2, 3); }
            fence_regs(hw);
            float s0 = 0.f, s1 = 0.f;
#pragma unroll
            for (int j = 0; j < 9; j++) { s0 += bf_lo(hw[2 * j]) + bf_hi(hw[2 * j]); s1 += bf_lo(hw[2 * j + 1]) + bf_hi(hw[2 * j + 1]); }
            s0 += __shfl_xor_sync(~0u, s0, 1); s0 += __shfl_xor_sync(~0u, s0, 2);
            s1 += __shfl_xor_sync(~0u, s1, 1); s1 += __shfl_xor_sync(~0u, s1, 2);
            const float m0 = s0 * (1.f / 72), m1 = s1 * (1.f / 72);
            float q0 = 0.f, q1 = 0.f;
#pragma unroll
            for (int j = 0; j < 9; j++) {
                const float a = bf_lo(hw[2 * j]) - m0, b = bf_hi(hw[2 * j]) - m0, c = bf_lo(hw[2 * j + 1]) - m1, d = bf_hi(hw[2 * j + 1]) - m1;
                q0 += a * a + b * b; q1 += c * c + d * d;
            }
            q0 += __shfl_xor_sync(~0u, q0, 1); q0 += __shfl_xor_sync(~0u, q0, 2);
            q1 += __shfl_xor_sync(~0u, q1, 1); q1 += __shfl_xor_sync(~0u, q1, 2);
            if (t == 0) {
                float2* ps = g_hstat + wsl * SEQ + wrb * 128 + warp * 16 + r;
                ps[0] = make_float2(s0, q0); ps[8] = make_float2(s1, q1);
            }
            __syncwarp();
            if (lane == 0) mbar_arrive(bar_hpub + 8);
        }
        uint32_t hreg[128];
        const uint32_t s_hx = sb + wg * C_HALF + ((e + 1) & 7) * 8192;
        float rstd0, rstd1;
        uint32_t mf0, mf1;
        uint32_t ph = 0;
        const uint32_t a_lo = desc_addr(sb + wg * C_HALF) | ((1024 >> 4) << 16);
#pragma unroll
        for (int pass = 0; pass < 3; pass++) {
            if (STAGGER >= 0 && wg == 1) nbar_sync(4, 256);
            float acc[96];
            float2 hs[4];
            const uint32_t b_lo = desc_addr(sb + C_OFF_W) | ((2048 >> 4) << 16);
#pragma unroll 1
            for (int i = 0; i < 3; i++) {
#pragma unroll
                for (int st = 0; st < 12; st++) {
                    if (pass == 0) {
                        const int n = 12 * i + st;
                        if ((2 * n + 1) / 9 != (2 * n - 1) / 9 || n == 0) mbar_wait(bar_h + 8 * ((2 * n + 1) / 9), 0);
                    }
                    mbar_wait(bar_full + 8 * st, ph);
                    if (tid == TCT && !(st & 1)) TC(2, 16 + pass * 18 + i * 6 + st / 2);
                    if (pass == 0 && st == 0 && i == 0 && tid == 0) TL(2, 5);
                    wg_fence();
                    mma_ss_n192(acc, a_lo + (12 * i + st) * 128, 128 >> 4, b_lo + st * (C_SLOT >> 4), HI_SW128, st > 0 ? 1u : (uint32_t)i);
                    wg_commit();
                    if (arm) mbar_expect(bar_full + 8 * st, C_SLOT);
                    if (st == STAGGER && wg == 0 && i == 0) nbar_arrive(4, 256);
                    if (pass == 0 && st == 0 && i == 2) {
                        mbar_wait(bar_hst, 0);
                        const float2* p = g_hstat + 2 * t * SEQ + rb * 128 + warp * 16 + r;
                        asm volatile("ld.global.cg.v2.f32 {%0, %1}, [%2];" : "=f"(hs[0].x), "=f"(hs[0].y) : "l"(p));
                        asm volatile("ld.global.cg.v2.f32 {%0, %1}, [%2];" : "=f"(hs[1].x), "=f"(hs[1].y) : "l"(p + SEQ));
                        asm volatile("ld.global.cg.v2.f32 {%0, %1}, [%2];" : "=f"(hs[2].x), "=f"(hs[2].y) : "l"(p + 8));
                        asm volatile("ld.global.cg.v2.f32 {%0, %1}, [%2];" : "=f"(hs[3].x), "=f"(hs[3].y) : "l"(p + SEQ + 8));
                    }
                    wg_wait<LAG>();
                    if ((((st + LAG) & 1) ? rel_odd : rel_even) && (st >= LAG || i > 0)) mbar_arrive_cluster(rel + 8 * ((st + 12 - LAG) % 12));
                }
                ph ^= 1;
            }
            if (pass == 0) {
                const RowStat s0 = combine_hstat(hs[0], hs[1]), s1 = combine_hstat(hs[2], hs[3]);
                rstd0 = s0.rstd; rstd1 = s1.rstd;
                mf0 = mean_frag(s0.mean, t); mf1 = mean_frag(s1.mean, t);
                mbar_wait(bar_cs, 0);
            }
            wg_fence();
            mma_rs_n192(acc, mf0, mf1, 0u, 0u, desc_addr(sb + C_OFF_CS) + pass * 192, 128 >> 4);
            wg_commit();
            if (LAG == 2) { wg_wait<2>(); if (rel_even) mbar_arrive_cluster(rel + 8 * 10); }
            wg_wait<1>();
            if (rel_odd) mbar_arrive_cluster(rel + 8 * 11);
            wg_wait<0>();
            fence_regs(acc);
            if (pass == 2 && rel_even) mbar_arrive(bar_g1);
            if (tid == 0) TL(2, 6 + pass);
#pragma unroll
            for (int j = 0; j < 48; j++) {
                const uint32_t w = pack_bf16_relu(acc[2 * j], acc[2 * j + 1]);
                if (pass * 48 + j < 128) hreg[(pass * 48 + j) & 127] = w;
                else sts32(s_hx + ((j - 32) >> 1) * 1024 + (warp & 3) * 256 + (j & 1) * 128 + lane * 4, w);
            }
        }
        fence_async_smem();
        nbar_sync(2 + wg, 128);
        fence_regs(hreg);
        const uint32_t b_lo = desc_addr(sb + C_OFF_W) | (1u << 16);
        const uint32_t stg = sb + wg * C_HALF + 65536;
        const uint32_t hx_lo = desc_addr(s_hx) | ((1024 >> 4) << 16);
        float acc0[32], acc1[32];
        auto gemm2_pass = [&](auto kind_tag, int p, float (&acc)[32], float (&prev)[32]) {
            constexpr int KIND = decltype(kind_tag)::value;
#pragma unroll
            for (int st = 0; st < 12; st++) {
                mbar_wait(bar_full + 8 * st, KIND != 1);
                if (tid == TCT && !(st & 1)) TC(2, 70 + p * 6 + st / 2);
                wg_fence();
#pragma unroll
                for (int j = 0; j < 3; j++) {
                    const int kk = st * 3 + j;
                    const uint32_t bl = b_lo + st * (C_SLOT >> 4) + j * 128;
                    if (kk < 32) mma_rs_n64(acc, hreg[(4 * kk) & 127], hreg[(4 * kk + 1) & 127], hreg[(4 * kk + 2) & 127], hreg[(4 * kk + 3) & 127], bl, HI_SW128, kk > 0 ? 1u : 0u);
                    else mma_ss_n64(acc, hx_lo + (kk - 32) * 128, 128 >> 4, bl, HI_SW128);
                }
                wg_commit();
                if (KIND < 2 && arm) mbar_expect(bar_full + 8 * st, C_SLOT);
                if (KIND == 2 && st >= 4 && st < 11 && st != 9) {
                    if (st == 4) {
                        mbar_wait(bar_recv, 0);
#pragma unroll
                        for (int i = 0; i < 32; i++) prev[i] = 0.f;
                    }
                    if (st == 10) mbar_wait(bar_wo, 1);
                    add_partial(prev, sb + wg * C_HALF + ((e + (st == 10 ? 2 : 3 - st)) & 7) * 8192 + (warp & 3) * 2048 + lane * 16);
                }
                if (st >= LAG || KIND == 1) wg_wait<LAG>();
                if ((st >= LAG ? KIND < 2 : KIND == 1) && (((st + LAG) & 1) ? rel_odd : rel_even)) mbar_arrive_cluster(rel + 8 * ((st + 12 - LAG) % 12));
                if (st == LAG - 1 && (KIND > 0 || p > 0)) {
                    fence_regs(prev);
                    uint4* dst = (uint4*)(g_part + (size_t)((rb * 9 + (p == 1 ? 8 : (e + p - 1) & 7)) * 8 + e) * 16384 + warp * 2048) + lane;
#pragma unroll
                    for (int i = 0; i < 4; i++)
                        dst[i * 32] = make_uint4(pack_bf16(prev[8 * i], prev[8 * i + 1]), pack_bf16(prev[8 * i + 2], prev[8 * i + 3]),
                                                 pack_bf16(prev[8 * i + 4], prev[8 * i + 5]), pack_bf16(prev[8 * i + 6], prev[8 * i + 7]));
                    __syncwarp();
                    if (lane == 0) mbar_arrive(bar_pub + 8 * (p - 1));
                }
            }
        };
#pragma unroll 1
        for (int p = 0; p < 8; p += 2) {
            gemm2_pass(std::integral_constant<int, 0>(), p, acc0, acc1);
            gemm2_pass(std::integral_constant<int, 1>(), p + 1, acc1, acc0);
            if (LAG == 2) { wg_wait<1>(); if (rel_even) mbar_arrive_cluster(rel + 8 * 10); }
            wg_wait<0>();
            fence_regs(acc1);
            if (rel_odd) mbar_arrive_cluster(rel + 8 * 11);
        }
        gemm2_pass(std::integral_constant<int, 2>(), 8, acc0, acc1);
        float (&acc)[32] = acc0, (&sum)[32] = acc1;
        const uint32_t hb = sb + wg * C_HALF + e * 8192 + (warp & 3) * 256 + lane * 4;
        uint32_t hv[16];
#pragma unroll
        for (int j = 0; j < 8; j++) { hv[2 * j] = lds32(hb + j * 1024); hv[2 * j + 1] = lds32(hb + j * 1024 + 128); }
        if (tid == 0) { TL(2, 9); TC(2, 9); }
        mbar_wait(bar_recv + 8, 0);
        if (tid == 0) { TL(2, 10); TC(2, 10); }
        add_partial(sum, stg + (warp & 3) * 2048 + lane * 16);
#pragma unroll
        for (int j = 0; j < 8; j++) {
            sum[4 * j] = fmaf(sum[4 * j], rstd0, bf_lo(hv[2 * j])); sum[4 * j + 1] = fmaf(sum[4 * j + 1], rstd0, bf_hi(hv[2 * j]));
            sum[4 * j + 2] = fmaf(sum[4 * j + 2], rstd1, bf_lo(hv[2 * j + 1])); sum[4 * j + 3] = fmaf(sum[4 * j + 3], rstd1, bf_hi(hv[2 * j + 1]));
        }
        fence_regs(sum);
        const uint32_t ob = stg + (warp & 3) * 2048 + (lane & 15) * 128;
        wg_wait<0>();
        fence_regs(acc);
#pragma unroll
        for (int j = 0; j < 8; j += 2)
            asm volatile("stmatrix.sync.aligned.m8n8.x4.shared.b16 [%0], {%1, %2, %3, %4};"
                         :: "r"(ob + (((j + (lane >> 4)) ^ (lane & 7)) << 4)),
                            "r"(pack_bf16(fmaf(acc[4 * j], rstd0, sum[4 * j]), fmaf(acc[4 * j + 1], rstd0, sum[4 * j + 1]))),
                            "r"(pack_bf16(fmaf(acc[4 * j + 2], rstd1, sum[4 * j + 2]), fmaf(acc[4 * j + 3], rstd1, sum[4 * j + 3]))),
                            "r"(pack_bf16(fmaf(acc[4 * j + 4], rstd0, sum[4 * j + 4]), fmaf(acc[4 * j + 5], rstd0, sum[4 * j + 5]))),
                            "r"(pack_bf16(fmaf(acc[4 * j + 6], rstd1, sum[4 * j + 6]), fmaf(acc[4 * j + 7], rstd1, sum[4 * j + 7]))) : "memory");
        fence_async_smem();
        __syncwarp();
        if (tid == 0) { TL(2, 11); TC(2, 11); }
        if (lane == 0) {
            tma_store_2d(&tm_out, stg + (warp & 3) * 2048, e * 64, rb * 128 + warp * 16);
            bulk_commit();
            bulk_wait_all();
            if (rel_even) { TL(2, 12 + wg); TC(2, 12 + wg); }
        }
    }
}

typedef CUresult (*EncodeFn)(CUtensorMap*, CUtensorMapDataType, cuuint32_t, void*, const cuuint64_t*, const cuuint64_t*,
                             const cuuint32_t*, const cuuint32_t*, CUtensorMapInterleave, CUtensorMapSwizzle,
                             CUtensorMapL2promotion, CUtensorMapFloatOOBfill);

void make_map(EncodeFn enc, CUtensorMap* m, const void* ptr, int cols, int rows, int box_c, int box_r, int chunks, CUtensorMapSwizzle sw,
              CUtensorMapL2promotion promo = CU_TENSOR_MAP_L2_PROMOTION_NONE) {
    const cuuint64_t dims[3] = {(cuuint64_t)cols, (cuuint64_t)rows, (cuuint64_t)chunks};
    const cuuint64_t strides[2] = {(cuuint64_t)cols * 2, (cuuint64_t)box_c * 2};
    const cuuint32_t box[3] = {(cuuint32_t)box_c, (cuuint32_t)box_r, (cuuint32_t)chunks};
    const cuuint32_t es[3] = {1, 1, 1};
    enc(m, CU_TENSOR_MAP_DATA_TYPE_BFLOAT16, chunks > 1 ? 3 : 2, (void*)ptr, dims, strides, box, es, CU_TENSOR_MAP_INTERLEAVE_NONE, sw,
        promo, CU_TENSOR_MAP_FLOAT_OOB_FILL_NONE);
}

}

extern "C" void kernel_launch(void* const* d_in, const int* in_sizes, int n_in, void* d_out, int out_size) {
    const __nv_bfloat16* x = (const __nv_bfloat16*)d_in[0];
    const __nv_bfloat16* wqkv = (const __nv_bfloat16*)d_in[1];
    const __nv_bfloat16* wo = (const __nv_bfloat16*)d_in[2];
    const __nv_bfloat16* w1 = (const __nv_bfloat16*)d_in[4];
    const __nv_bfloat16* w2 = (const __nv_bfloat16*)d_in[5];

    void* fn = nullptr;
    cudaDriverEntryPointQueryResult qr;
    cudaGetDriverEntryPoint("cuTensorMapEncodeTiled", &fn, cudaEnableDefault, &qr);
    EncodeFn enc = (EncodeFn)fn;
    void* p_attn = nullptr;
    cudaGetSymbolAddress(&p_attn, g_attn);
    CUtensorMap tm_x, tm_wqkv, tm_wo, tm_wo2, tm_ast, tm_attn, tm_w1, tm_w2, tm_out;
    make_map(enc, &tm_x, x, DM, SEQ, 64, 128, 1, CU_TENSOR_MAP_SWIZZLE_128B, PROMO_X);
    make_map(enc, &tm_wqkv, wqkv, 1728, DM, 32, 16, 7, CU_TENSOR_MAP_SWIZZLE_64B, PROMO_W);
    {
        const cuuint64_t dims[4] = {DM, 16, 9, 32}, strides[3] = {DM * 2, 16, 18 * DM * 2};
        const cuuint32_t box[4] = {8, 16, 9, 16}, es[5] = {1, 1, 1, 1, 1};
        enc(&tm_wo, CU_TENSOR_MAP_DATA_TYPE_BFLOAT16, 4, (void*)wo, dims, strides, box, es, CU_TENSOR_MAP_INTERLEAVE_NONE,
            CU_TENSOR_MAP_SWIZZLE_NONE, CU_TENSOR_MAP_L2_PROMOTION_NONE, CU_TENSOR_MAP_FLOAT_OOB_FILL_NONE);
        const cuuint64_t dims2[5] = {DM, 2, 8, 9, 4}, strides2[4] = {DM * 2, 18 * DM * 2, 16, 144 * DM * 2};
        const cuuint32_t box2[5] = {8, 2, 8, 9, 4};
        enc(&tm_wo2, CU_TENSOR_MAP_DATA_TYPE_BFLOAT16, 5, (void*)(wo + 16 * DM), dims2, strides2, box2, es, CU_TENSOR_MAP_INTERLEAVE_NONE,
            CU_TENSOR_MAP_SWIZZLE_NONE, CU_TENSOR_MAP_L2_PROMOTION_NONE, CU_TENSOR_MAP_FLOAT_OOB_FILL_NONE);
    }
    make_map(enc, &tm_attn, p_attn, 512, SEQ, 64, 64, 1, CU_TENSOR_MAP_SWIZZLE_128B);
    make_map(enc, &tm_ast, p_attn, 512, SEQ, 16, 32, 1, CU_TENSOR_MAP_SWIZZLE_NONE);
    make_map(enc, &tm_w1, w1, FF, DM, 64, 16, 3, CU_TENSOR_MAP_SWIZZLE_128B);
    make_map(enc, &tm_w2, w2, DM, FF, 64, 48, 1, CU_TENSOR_MAP_SWIZZLE_128B);
    make_map(enc, &tm_out, d_out, DM, SEQ, 64, 16, 1, CU_TENSOR_MAP_SWIZZLE_128B);

    cudaFuncSetAttribute(qkv_kernel, cudaFuncAttributeMaxDynamicSharedMemorySize, A_SMEM);
    cudaFuncSetAttribute(attn_kernel, cudaFuncAttributeMaxDynamicSharedMemorySize, B_SMEM);
    cudaFuncSetAttribute(ffn_kernel, cudaFuncAttributeMaxDynamicSharedMemorySize, C_SMEM);

    cudaLaunchAttribute at[2];
    at[0].id = cudaLaunchAttributeClusterDimension;
    at[0].val.clusterDim.x = 2; at[0].val.clusterDim.y = 1; at[0].val.clusterDim.z = 1;
    at[1].id = cudaLaunchAttributeProgrammaticStreamSerialization;
    at[1].val.programmaticStreamSerializationAllowed = 1;

    cudaLaunchConfig_t cfg = {};
    cfg.stream = cudaStreamPerThread;
    cfg.gridDim = 128; cfg.blockDim = 384; cfg.dynamicSmemBytes = A_SMEM; cfg.attrs = at; cfg.numAttrs = 1;
    cudaLaunchKernelEx(&cfg, qkv_kernel, tm_x, tm_wqkv, x);
    cfg.gridDim = 132; cfg.blockDim = 512; cfg.dynamicSmemBytes = B_SMEM; cfg.attrs = at + 1; cfg.numAttrs = 1;
    cudaLaunchKernelEx(&cfg, attn_kernel, tm_wo, tm_wo2, tm_ast, w1, w2);
    cfg.gridDim = 128; cfg.blockDim = 384; cfg.dynamicSmemBytes = C_SMEM; cfg.attrs = at; cfg.numAttrs = 2;
    cudaLaunchKernelEx(&cfg, ffn_kernel, tm_attn, tm_w1, tm_w2, tm_out, x, (__nv_bfloat16*)d_out);
}
```

```cpp
#include <cuda_runtime.h>
#include <cuda_bf16.h>
#include <cuda.h>
#include <stdint.h>
#include <type_traits>

#define EARLY7 1
#define ONEPASS 0
namespace {

constexpr int SEQ = 2048, DM = 576, FF = 4608;
constexpr float LN_EPS = 1e-5f;
constexpr float QSCALE = 0.34004648f;

constexpr int BLK_BYTES = 6144;
constexpr int SLOT_BYTES = 16 * BLK_BYTES;
constexpr uint32_t POLY_PATTERN = 0xB5B5u;

__device__ __align__(1024) uint8_t g_qkv[96 * SLOT_BYTES];
__device__ __align__(1024) __nv_bfloat16 g_attn[SEQ * 512];
__device__ __align__(1024) uint32_t g_rem[32 * SEQ];
__device__ __align__(1024) uint8_t g_h[16 * 147456];
__device__ __align__(1024) uint8_t g_wo_img[8 * 82944];
__device__ __align__(1024) uint8_t g_part[16 * 9 * 8 * 16384];
__device__ __align__(128) float g_cs0[8 * 16 * 216];
__device__ __align__(128) uint8_t g_cs1[FF / 8 * 128];
__device__ __align__(128) float2 g_xstat[SEQ];
__device__ __align__(128) float2 g_hstat[8 * SEQ];
__device__ __align__(16) float g_kmax[8 * 128];
constexpr int FLAG_H = 0, FLAG_HST = 128, FLAG_PART = 144, N_FLAG_C = FLAG_PART + 16 * 9 * 8;
static_assert(N_FLAG_C <= 128 * 12, "kernel A clears 12 flags per CTA");
__device__ unsigned int g_flag_c[N_FLAG_C];

constexpr uint32_t SPIN_LIMIT = 1u << 18;
constexpr uint32_t SUSPEND_NS = 20;

__device__ __forceinline__ uint32_t smem_u32(const void* p) { return (uint32_t)__cvta_generic_to_shared(p); }
__device__ __forceinline__ void mbar_init(uint32_t bar, uint32_t cnt) { asm volatile("mbarrier.init.shared::cta.b64 [%0], %1;" :: "r"(bar), "r"(cnt) : "memory"); }
__device__ __forceinline__ void mbar_expect(uint32_t bar, uint32_t bytes) { asm volatile("mbarrier.arrive.expect_tx.shared::cta.b64 _, [%0], %1;" :: "r"(bar), "r"(bytes) : "memory"); }
__device__ __forceinline__ void mbar_arrive(uint32_t bar) { asm volatile("mbarrier.arrive.shared::cta.b64 _, [%0];" :: "r"(bar) : "memory"); }
__device__ __forceinline__ void mbar_arrive_cluster(uint32_t bar) { asm volatile("mbarrier.arrive.shared::cluster.b64 _, [%0];" :: "r"(bar) : "memory"); }
__device__ __forceinline__ void mbar_wait(uint32_t bar, uint32_t parity, uint32_t& budget) {
    asm volatile("{\n.reg .pred p;\nWAIT_LOOP:\nmbarrier.try_wait.parity.shared::cta.b64 p, [%1], %2;\n@p bra.uni WAIT_DONE;\n"
                 "add.u32 %0, %0, 1;\nsetp.lt.u32 p, %0, %3;\n@p bra.uni WAIT_LOOP;\nWAIT_DONE:\n}\n"
                 : "+r"(budget) : "r"(bar), "r"(parity), "n"(SPIN_LIMIT * 16) : "memory");
}
__device__ __forceinline__ void mbar_wait_trap(uint32_t bar, uint32_t parity) {
    for (uint32_t i = 0;; i++) {
        uint32_t ok;
        asm volatile("{\n.reg .pred p;\nmbarrier.try_wait.parity.shared::cta.b64 p, [%1], %2, %3;\nselp.u32 %0, 1, 0, p;\n}\n"
                     : "=r"(ok) : "r"(bar), "r"(parity), "r"(SUSPEND_NS) : "memory");
        if (ok) break;
        if (i > SPIN_LIMIT) __trap();
    }
}
__device__ __forceinline__ uint32_t mapa(uint32_t addr, uint32_t rank) { uint32_t r; asm("mapa.shared::cluster.u32 %0, %1, %2;" : "=r"(r) : "r"(addr), "r"(rank)); return r; }
__device__ __forceinline__ void cluster_sync() { asm volatile("barrier.cluster.arrive.relaxed.aligned;\nbarrier.cluster.wait.aligned;" ::: "memory"); }
__device__ __forceinline__ void fence_mbar_init() { asm volatile("fence.mbarrier_init.release.cluster;" ::: "memory"); }
__device__ __forceinline__ void fence_async_smem() { asm volatile("fence.proxy.async.shared::cta;" ::: "memory"); }
__device__ __forceinline__ void nbar_sync(uint32_t id, uint32_t n) { asm volatile("bar.sync %0, %1;" :: "r"(id), "r"(n) : "memory"); }
__device__ __forceinline__ void nbar_arrive(uint32_t id, uint32_t n) { asm volatile("bar.arrive %0, %1;" :: "r"(id), "r"(n) : "memory"); }
__device__ __forceinline__ void pdl_wait() { asm volatile("griddepcontrol.wait;" ::: "memory"); }
__device__ __forceinline__ void pdl_launch() { asm volatile("griddepcontrol.launch_dependents;" ::: "memory"); }
__device__ __forceinline__ void flag_add(unsigned int* p) {
    asm volatile("fence.proxy.async.global;\nred.release.gpu.global.add.u32 [%0], 1;" :: "l"(p) : "memory");
}
__device__ __forceinline__ void flag_acquire() { asm volatile("fence.acquire.gpu;\nfence.proxy.async.global;" ::: "memory"); }
__device__ __forceinline__ uint32_t flag_read(const unsigned int* p) {
    uint32_t v;
    asm volatile("ld.relaxed.gpu.global.u32 %0, [%1];" : "=r"(v) : "l"(p) : "memory");
    return v;
}
__device__ __forceinline__ void st_strong(void* p, uint32_t a, uint32_t b) { asm volatile("st.relaxed.gpu.global.v2.b32 [%0], {%1, %2};" :: "l"(p), "r"(a), "r"(b) : "memory"); }
__device__ __forceinline__ uint4 ld_strong(const void* p) {
    uint4 v;
    asm volatile("ld.relaxed.gpu.global.v4.b32 {%0, %1, %2, %3}, [%4];" : "=r"(v.x), "=r"(v.y), "=r"(v.z), "=r"(v.w) : "l"(p) : "memory");
    return v;
}
__device__ __forceinline__ void flag_wait(const unsigned int* p, uint32_t target) {
    for (uint32_t i = 0; flag_read(p) < target; i++) if (i > SPIN_LIMIT) __trap();
    flag_acquire();
}
__device__ __forceinline__ uint32_t flag_poll(const unsigned int* p, bool active, uint32_t target) {
    return __ballot_sync(~0u, active && flag_read(p) >= target);
}
__device__ __forceinline__ void bulk_load(uint32_t dst, const void* src, uint32_t bytes, uint32_t bar) {
    asm volatile("cp.async.bulk.shared::cluster.global.mbarrier::complete_tx::bytes [%0], [%1], %2, [%3];" :: "r"(dst), "l"(src), "r"(bytes), "r"(bar) : "memory");
}
__device__ __forceinline__ void bulk_store(void* dst, uint32_t src, uint32_t bytes) {
    asm volatile("cp.async.bulk.global.shared::cta.bulk_group [%0], [%1], %2;" :: "l"(dst), "r"(src), "r"(bytes) : "memory");
}
__device__ __forceinline__ void bulk_commit() { asm volatile("cp.async.bulk.commit_group;" ::: "memory"); }
__device__ __forceinline__ void bulk_wait_all() { asm volatile("cp.async.bulk.wait_group 0;" ::: "memory"); }
__device__ __forceinline__ void tma_2d(uint32_t dst, const CUtensorMap* m, int c0, int c1, uint32_t bar) {
    asm volatile("cp.async.bulk.tensor.2d.shared::cluster.global.mbarrier::complete_tx::bytes [%0], [%1, {%3, %4}], [%2];"
                 :: "r"(dst), "l"(m), "r"(bar), "r"(c0), "r"(c1) : "memory");
}
__device__ __forceinline__ void tma_2d_mc(uint32_t dst, const CUtensorMap* m, int c0, int c1, uint32_t bar) {
    asm volatile("cp.async.bulk.tensor.2d.shared::cluster.global.mbarrier::complete_tx::bytes.multicast::cluster [%0], [%1, {%3, %4}], [%2], %5;"
                 :: "r"(dst), "l"(m), "r"(bar), "r"(c0), "r"(c1), "h"((uint16_t)3) : "memory");
}
__device__ __forceinline__ void tma_3d_mc(uint32_t dst, const CUtensorMap* m, int c0, int c1, uint32_t bar) {
    asm volatile("cp.async.bulk.tensor.3d.shared::cluster.global.mbarrier::complete_tx::bytes.multicast::cluster [%0], [%1, {%3, %4, %5}], [%2], %6;"
                 :: "r"(dst), "l"(m), "r"(bar), "r"(c0), "r"(c1), "r"(0), "h"((uint16_t)3) : "memory");
}
__device__ __forceinline__ void tma_store_2d(const CUtensorMap* m, uint32_t src, int c0, int c1) {
    asm volatile("cp.async.bulk.tensor.2d.global.shared::cta.bulk_group [%0, {%2, %3}], [%1];" :: "l"(m), "r"(src), "r"(c0), "r"(c1) : "memory");
}
__device__ __forceinline__ void tma_prefetch_desc(const CUtensorMap* m) { asm volatile("prefetch.tensormap [%0];" :: "l"(m) : "memory"); }
__device__ __forceinline__ void wg_fence() { asm volatile("wgmma.fence.sync.aligned;" ::: "memory"); }
__device__ __forceinline__ void wg_commit() { asm volatile("wgmma.commit_group.sync.aligned;" ::: "memory"); }
template <int N> __device__ __forceinline__ void wg_wait() { asm volatile("wgmma.wait_group.sync.aligned %0;" :: "n"(N) : "memory"); }
template <int N> __device__ __forceinline__ void fence_regs(float (&d)[N]) {
#pragma unroll
    for (int i = 0; i < N; i++) asm volatile("" : "+f"(d[i]) :: "memory");
}
template <int N> __device__ __forceinline__ void fence_regs(uint32_t (&d)[N]) {
#pragma unroll
    for (int i = 0; i < N; i++) asm volatile("" : "+r"(d[i]) :: "memory");
}
__device__ __forceinline__ uint32_t pack_bf16(float lo, float hi) { uint32_t r; asm("cvt.rn.bf16x2.f32 %0, %1, %2;" : "=r"(r) : "f"(hi), "f"(lo)); return r; }
__device__ __forceinline__ uint32_t pack_bf16_relu(float lo, float hi) { uint32_t r; asm("cvt.rn.relu.bf16x2.f32 %0, %1, %2;" : "=r"(r) : "f"(hi), "f"(lo)); return r; }
__device__ __forceinline__ float bf_lo(uint32_t w) { return __uint_as_float(w << 16); }
__device__ __forceinline__ float bf_hi(uint32_t w) { return __uint_as_float(w & 0xFFFF0000u); }
__device__ __forceinline__ float ex2(float x) { float r; asm("ex2.approx.ftz.f32 %0, %1;" : "=f"(r) : "f"(x)); return r; }
__device__ __forceinline__ void sts32(uint32_t a, uint32_t v) { asm volatile("st.shared.b32 [%0], %1;" :: "r"(a), "r"(v) : "memory"); }
__device__ __forceinline__ void sts64f(uint32_t a, float x, float y) { asm volatile("st.shared.v2.f32 [%0], {%1, %2};" :: "r"(a), "f"(x), "f"(y) : "memory"); }
__device__ __forceinline__ void sts128(uint32_t a, uint32_t x, uint32_t y, uint32_t z, uint32_t w) { asm volatile("st.shared.v4.b32 [%0], {%1, %2, %3, %4};" :: "r"(a), "r"(x), "r"(y), "r"(z), "r"(w) : "memory"); }
__device__ __forceinline__ uint32_t lds32(uint32_t a) { uint32_t v; asm volatile("ld.shared.b32 %0, [%1];" : "=r"(v) : "r"(a) : "memory"); return v; }
__device__ __forceinline__ float2 lds64f(uint32_t a) { float2 v; asm volatile("ld.shared.v2.f32 {%0, %1}, [%2];" : "=f"(v.x), "=f"(v.y) : "r"(a) : "memory"); return v; }
__device__ __forceinline__ uint4 lds128(uint32_t a) { uint4 v; asm volatile("ld.shared.v4.b32 {%0, %1, %2, %3}, [%4];" : "=r"(v.x), "=r"(v.y), "=r"(v.z), "=r"(v.w) : "r"(a) : "memory"); return v; }

__device__ __forceinline__ uint32_t desc_addr(uint32_t a) { return (a & 0x3FFFFu) >> 4; }
constexpr uint32_t HI_SW128 = (1024 >> 4) | (1u << 30);
constexpr uint32_t HI_SW64 = (512 >> 4) | (2u << 30);

__device__ __forceinline__ void mma_ss_n224(float (&d)[112], uint32_t alo, uint32_t ahi, uint32_t blo, uint32_t bhi, uint32_t acc) {
    asm volatile("{\n.reg .b64 da, db;\n.reg .pred p;\nsetp.ne.u32 p, %116, 0;\nmov.b64 da, {%112, %113};\nmov.b64 db, {%114, %115};\n"
        "wgmma.mma_async.sync.aligned.m64n224k16.f32.bf16.bf16 "
        "{%0, %1, %2, %3, %4, %5, %6, %7, %8, %9, %10, %11, %12, %13, %14, %15, "
        "%16, %17, %18, %19, %20, %21, %22, %23, %24, %25, %26, %27, %28, %29, %30, %31, "
        "%32, %33, %34, %35, %36, %37, %38, %39, %40, %41, %42, %43, %44, %45, %46, %47, "
        "%48, %49, %50, %51, %52, %53, %54, %55, %56, %57, %58, %59, %60, %61, %62, %63, "
        "%64, %65, %66, %67, %68, %69, %70, %71, %72, %73, %74, %75, %76, %77, %78, %79, "
        "%80, %81, %82, %83, %84, %85, %86, %87, %88, %89, %90, %91, %92, %93, %94, %95, "
        "%96, %97, %98, %99, %100, %101, %102, %103, %104, %105, %106, %107, %108, %109, %110, %111}, "
        "da, db, p, 1, 1, 0, 1;\n}\n"
        : "+f"(d[0]), "+f"(d[1]), "+f"(d[2]), "+f"(d[3]), "+f"(d[4]), "+f"(d[5]), "+f"(d[6]), "+f"(d[7]),
          "+f"(d[8]), "+f"(d[9]), "+f"(d[10]), "+f"(d[11]), "+f"(d[12]), "+f"(d[13]), "+f"(d[14]), "+f"(d[15]),
          "+f"(d[16]), "+f"(d[17]), "+f"(d[18]), "+f"(d[19]), "+f"(d[20]), "+f"(d[21]), "+f"(d[22]), "+f"(d[23]),
          "+f"(d[24]), "+f"(d[25]), "+f"(d[26]), "+f"(d[27]), "+f"(d[28]), "+f"(d[29]), "+f"(d[30]), "+f"(d[31]),
          "+f"(d[32]), "+f"(d[33]), "+f"(d[34]), "+f"(d[35]), "+f"(d[36]), "+f"(d[37]), "+f"(d[38]), "+f"(d[39]),
          "+f"(d[40]), "+f"(d[41]), "+f"(d[42]), "+f"(d[43]), "+f"(d[44]), "+f"(d[45]), "+f"(d[46]), "+f"(d[47]),
          "+f"(d[48]), "+f"(d[49]), "+f"(d[50]), "+f"(d[51]), "+f"(d[52]), "+f"(d[53]), "+f"(d[54]), "+f"(d[55]),
          "+f"(d[56]), "+f"(d[57]), "+f"(d[58]), "+f"(d[59]), "+f"(d[60]), "+f"(d[61]), "+f"(d[62]), "+f"(d[63]),
          "+f"(d[64]), "+f"(d[65]), "+f"(d[66]), "+f"(d[67]), "+f"(d[68]), "+f"(d[69]), "+f"(d[70]), "+f"(d[71]),
          "+f"(d[72]), "+f"(d[73]), "+f"(d[74]), "+f"(d[75]), "+f"(d[76]), "+f"(d[77]), "+f"(d[78]), "+f"(d[79]),
          "+f"(d[80]), "+f"(d[81]), "+f"(d[82]), "+f"(d[83]), "+f"(d[84]), "+f"(d[85]), "+f"(d[86]), "+f"(d[87]),
          "+f"(d[88]), "+f"(d[89]), "+f"(d[90]), "+f"(d[91]), "+f"(d[92]), "+f"(d[93]), "+f"(d[94]), "+f"(d[95]),
          "+f"(d[96]), "+f"(d[97]), "+f"(d[98]), "+f"(d[99]), "+f"(d[100]), "+f"(d[101]), "+f"(d[102]), "+f"(d[103]),
          "+f"(d[104]), "+f"(d[105]), "+f"(d[106]), "+f"(d[107]), "+f"(d[108]), "+f"(d[109]), "+f"(d[110]), "+f"(d[111])
        : "r"(alo), "r"(ahi), "r"(blo), "r"(bhi), "r"(acc));
}
__device__ __forceinline__ void mma_qk_first(float (&d)[32], uint32_t a0, uint32_t a1, uint32_t a2, uint32_t a3, uint64_t db) {
    asm volatile("wgmma.mma_async.sync.aligned.m64n64k16.f32.bf16.bf16 "
        "{%0, %1, %2, %3, %4, %5, %6, %7, %8, %9, %10, %11, %12, %13, %14, %15, "
        "%16, %17, %18, %19, %20, %21, %22, %23, %24, %25, %26, %27, %28, %29, %30, %31}, "
        "{%32, %33, %34, %35}, %36, 0, 1, 1, 0;"
        : "=f"(d[0]), "=f"(d[1]), "=f"(d[2]), "=f"(d[3]), "=f"(d[4]), "=f"(d[5]), "=f"(d[6]), "=f"(d[7]),
          "=f"(d[8]), "=f"(d[9]), "=f"(d[10]), "=f"(d[11]), "=f"(d[12]), "=f"(d[13]), "=f"(d[14]), "=f"(d[15]),
          "=f"(d[16]), "=f"(d[17]), "=f"(d[18]), "=f"(d[19]), "=f"(d[20]), "=f"(d[21]), "=f"(d[22]), "=f"(d[23]),
          "=f"(d[24]), "=f"(d[25]), "=f"(d[26]), "=f"(d[27]), "=f"(d[28]), "=f"(d[29]), "=f"(d[30]), "=f"(d[31])
        : "r"(a0), "r"(a1), "r"(a2), "r"(a3), "l"(db));
}
__device__ __forceinline__ void mma_qk_second(float (&d)[32], uint32_t a0, uint32_t a1, uint32_t a2, uint32_t a3, uint64_t db) {
    asm volatile("wgmma.mma_async.sync.aligned.m64n64k16.f32.bf16.bf16 "
        "{%0, %1, %2, %3, %4, %5, %6, %7, %8, %9, %10, %11, %12, %13, %14, %15, "
        "%16, %17, %18, %19, %20, %21, %22, %23, %24, %25, %26, %27, %28, %29, %30, %31}, "
        "{%32, %33, %34, %35}, %36, 1, 1, 1, 0;"
        : "+f"(d[0]), "+f"(d[1]), "+f"(d[2]), "+f"(d[3]), "+f"(d[4]), "+f"(d[5]), "+f"(d[6]), "+f"(d[7]),
          "+f"(d[8]), "+f"(d[9]), "+f"(d[10]), "+f"(d[11]), "+f"(d[12]), "+f"(d[13]), "+f"(d[14]), "+f"(d[15]),
          "+f"(d[16]), "+f"(d[17]), "+f"(d[18]), "+f"(d[19]), "+f"(d[20]), "+f"(d[21]), "+f"(d[22]), "+f"(d[23]),
          "+f"(d[24]), "+f"(d[25]), "+f"(d[26]), "+f"(d[27]), "+f"(d[28]), "+f"(d[29]), "+f"(d[30]), "+f"(d[31])
        : "r"(a0), "r"(a1), "r"(a2), "r"(a3), "l"(db));
}
__device__ __forceinline__ void mma_pv(float (&d)[12], uint32_t a0, uint32_t a1, uint32_t a2, uint32_t a3, uint64_t db) {
    asm volatile("wgmma.mma_async.sync.aligned.m64n24k16.f32.bf16.bf16 "
        "{%0, %1, %2, %3, %4, %5, %6, %7, %8, %9, %10, %11}, "
        "{%12, %13, %14, %15}, %16, 1, 1, 1, 1;"
        : "+f"(d[0]), "+f"(d[1]), "+f"(d[2]), "+f"(d[3]), "+f"(d[4]), "+f"(d[5]), "+f"(d[6]), "+f"(d[7]),
          "+f"(d[8]), "+f"(d[9]), "+f"(d[10]), "+f"(d[11])
        : "r"(a0), "r"(a1), "r"(a2), "r"(a3), "l"(db));
}
__device__ __forceinline__ void mma_ss_n72(float (&d)[36], uint32_t alo, uint32_t ahi, uint32_t blo, uint32_t bhi, uint32_t acc) {
    asm volatile("{\n.reg .b64 da, db;\n.reg .pred p;\nsetp.ne.u32 p, %40, 0;\nmov.b64 da, {%36, %37};\nmov.b64 db, {%38, %39};\n"
        "wgmma.mma_async.sync.aligned.m64n72k16.f32.bf16.bf16 "
        "{%0, %1, %2, %3, %4, %5, %6, %7, %8, %9, %10, %11, %12, %13, %14, %15, "
        "%16, %17, %18, %19, %20, %21, %22, %23, %24, %25, %26, %27, %28, %29, %30, %31, "
        "%32, %33, %34, %35}, "
        "da, db, p, 1, 1, 0, 1;\n}\n"
        : "+f"(d[0]), "+f"(d[1]), "+f"(d[2]), "+f"(d[3]), "+f"(d[4]), "+f"(d[5]), "+f"(d[6]), "+f"(d[7]),
          "+f"(d[8]), "+f"(d[9]), "+f"(d[10]), "+f"(d[11]), "+f"(d[12]), "+f"(d[13]), "+f"(d[14]), "+f"(d[15]),
          "+f"(d[16]), "+f"(d[17]), "+f"(d[18]), "+f"(d[19]), "+f"(d[20]), "+f"(d[21]), "+f"(d[22]), "+f"(d[23]),
          "+f"(d[24]), "+f"(d[25]), "+f"(d[26]), "+f"(d[27]), "+f"(d[28]), "+f"(d[29]), "+f"(d[30]), "+f"(d[31]),
          "+f"(d[32]), "+f"(d[33]), "+f"(d[34]), "+f"(d[35])
        : "r"(alo), "r"(ahi), "r"(blo), "r"(bhi), "r"(acc));
}
__device__ __forceinline__ void mma_ss_n192(float (&d)[96], uint32_t alo, uint32_t ahi, uint32_t blo, uint32_t bhi, uint32_t acc) {
    asm volatile("{\n.reg .b64 da, db;\n.reg .pred p;\nsetp.ne.u32 p, %100, 0;\nmov.b64 da, {%96, %97};\nmov.b64 db, {%98, %99};\n"
        "wgmma.mma_async.sync.aligned.m64n192k16.f32.bf16.bf16 "
        "{%0, %1, %2, %3, %4, %5, %6, %7, %8, %9, %10, %11, %12, %13, %14, %15, "
        "%16, %17, %18, %19, %20, %21, %22, %23, %24, %25, %26, %27, %28, %29, %30, %31, "
        "%32, %33, %34, %35, %36, %37, %38, %39, %40, %41, %42, %43, %44, %45, %46, %47, "
        "%48, %49, %50, %51, %52, %53, %54, %55, %56, %57, %58, %59, %60, %61, %62, %63, "
        "%64, %65, %66, %67, %68, %69, %70, %71, %72, %73, %74, %75, %76, %77, %78, %79, "
        "%80, %81, %82, %83, %84, %85, %86, %87, %88, %89, %90, %91, %92, %93, %94, %95}, "
        "da, db, p, 1, 1, 0, 1;\n}\n"
        : "+f"(d[0]), "+f"(d[1]), "+f"(d[2]), "+f"(d[3]), "+f"(d[4]), "+f"(d[5]), "+f"(d[6]), "+f"(d[7]),
          "+f"(d[8]), "+f"(d[9]), "+f"(d[10]), "+f"(d[11]), "+f"(d[12]), "+f"(d[13]), "+f"(d[14]), "+f"(d[15]),
          "+f"(d[16]), "+f"(d[17]), "+f"(d[18]), "+f"(d[19]), "+f"(d[20]), "+f"(d[21]), "+f"(d[22]), "+f"(d[23]),
          "+f"(d[24]), "+f"(d[25]), "+f"(d[26]), "+f"(d[27]), "+f"(d[28]), "+f"(d[29]), "+f"(d[30]), "+f"(d[31]),
          "+f"(d[32]), "+f"(d[33]), "+f"(d[34]), "+f"(d[35]), "+f"(d[36]), "+f"(d[37]), "+f"(d[38]), "+f"(d[39]),
          "+f"(d[40]), "+f"(d[41]), "+f"(d[42]), "+f"(d[43]), "+f"(d[44]), "+f"(d[45]), "+f"(d[46]), "+f"(d[47]),
          "+f"(d[48]), "+f"(d[49]), "+f"(d[50]), "+f"(d[51]), "+f"(d[52]), "+f"(d[53]), "+f"(d[54]), "+f"(d[55]),
          "+f"(d[56]), "+f"(d[57]), "+f"(d[58]), "+f"(d[59]), "+f"(d[60]), "+f"(d[61]), "+f"(d[62]), "+f"(d[63]),
          "+f"(d[64]), "+f"(d[65]), "+f"(d[66]), "+f"(d[67]), "+f"(d[68]), "+f"(d[69]), "+f"(d[70]), "+f"(d[71]),
          "+f"(d[72]), "+f"(d[73]), "+f"(d[74]), "+f"(d[75]), "+f"(d[76]), "+f"(d[77]), "+f"(d[78]), "+f"(d[79]),
          "+f"(d[80]), "+f"(d[81]), "+f"(d[82]), "+f"(d[83]), "+f"(d[84]), "+f"(d[85]), "+f"(d[86]), "+f"(d[87]),
          "+f"(d[88]), "+f"(d[89]), "+f"(d[90]), "+f"(d[91]), "+f"(d[92]), "+f"(d[93]), "+f"(d[94]), "+f"(d[95])
        : "r"(alo), "r"(ahi), "r"(blo), "r"(bhi), "r"(acc));
}
__device__ __forceinline__ void mma_rs_n64(float (&d)[32], uint32_t a0, uint32_t a1, uint32_t a2, uint32_t a3, uint32_t blo, uint32_t bhi, uint32_t acc) {
    asm volatile("{\n.reg .b64 da, db;\n.reg .pred p;\nsetp.ne.u32 p, %38, 0;\nmov.b64 db, {%36, %37};\n"
        "wgmma.mma_async.sync.aligned.m64n64k16.f32.bf16.bf16 "
        "{%0, %1, %2, %3, %4, %5, %6, %7, %8, %9, %10, %11, %12, %13, %14, %15, "
        "%16, %17, %18, %19, %20, %21, %22, %23, %24, %25, %26, %27, %28, %29, %30, %31}, "
        "{%32, %33, %34, %35}, db, p, 1, 1, 1;\n}\n"
        : "+f"(d[0]), "+f"(d[1]), "+f"(d[2]), "+f"(d[3]), "+f"(d[4]), "+f"(d[5]), "+f"(d[6]), "+f"(d[7]),
          "+f"(d[8]), "+f"(d[9]), "+f"(d[10]), "+f"(d[11]), "+f"(d[12]), "+f"(d[13]), "+f"(d[14]), "+f"(d[15]),
          "+f"(d[16]), "+f"(d[17]), "+f"(d[18]), "+f"(d[19]), "+f"(d[20]), "+f"(d[21]), "+f"(d[22]), "+f"(d[23]),
          "+f"(d[24]), "+f"(d[25]), "+f"(d[26]), "+f"(d[27]), "+f"(d[28]), "+f"(d[29]), "+f"(d[30]), "+f"(d[31])
        : "r"(a0), "r"(a1), "r"(a2), "r"(a3), "r"(blo), "r"(bhi), "r"(acc));
}
__device__ __forceinline__ void mma_rs_n192(float (&d)[96], uint32_t a0, uint32_t a1, uint32_t a2, uint32_t a3, uint32_t blo, uint32_t bhi) {
    asm volatile("{\n.reg .b64 da, db;\nmov.b64 db, {%100, %101};\n"
        "wgmma.mma_async.sync.aligned.m64n192k16.f32.bf16.bf16 "
        "{%0, %1, %2, %3, %4, %5, %6, %7, %8, %9, %10, %11, %12, %13, %14, %15, "
        "%16, %17, %18, %19, %20, %21, %22, %23, %24, %25, %26, %27, %28, %29, %30, %31, "
        "%32, %33, %34, %35, %36, %37, %38, %39, %40, %41, %42, %43, %44, %45, %46, %47, "
        "%48, %49, %50, %51, %52, %53, %54, %55, %56, %57, %58, %59, %60, %61, %62, %63, "
        "%64, %65, %66, %67, %68, %69, %70, %71, %72, %73, %74, %75, %76, %77, %78, %79, "
        "%80, %81, %82, %83, %84, %85, %86, %87, %88, %89, %90, %91, %92, %93, %94, %95}, "
        "{%96, %97, %98, %99}, db, 1, 1, 1, 1;\n}\n"
        : "+f"(d[0]), "+f"(d[1]), "+f"(d[2]), "+f"(d[3]), "+f"(d[4]), "+f"(d[5]), "+f"(d[6]), "+f"(d[7]),
          "+f"(d[8]), "+f"(d[9]), "+f"(d[10]), "+f"(d[11]), "+f"(d[12]), "+f"(d[13]), "+f"(d[14]), "+f"(d[15]),
          "+f"(d[16]), "+f"(d[17]), "+f"(d[18]), "+f"(d[19]), "+f"(d[20]), "+f"(d[21]), "+f"(d[22]), "+f"(d[23]),
          "+f"(d[24]), "+f"(d[25]), "+f"(d[26]), "+f"(d[27]), "+f"(d[28]), "+f"(d[29]), "+f"(d[30]), "+f"(d[31]),
          "+f"(d[32]), "+f"(d[33]), "+f"(d[34]), "+f"(d[35]), "+f"(d[36]), "+f"(d[37]), "+f"(d[38]), "+f"(d[39]),
          "+f"(d[40]), "+f"(d[41]), "+f"(d[42]), "+f"(d[43]), "+f"(d[44]), "+f"(d[45]), "+f"(d[46]), "+f"(d[47]),
          "+f"(d[48]), "+f"(d[49]), "+f"(d[50]), "+f"(d[51]), "+f"(d[52]), "+f"(d[53]), "+f"(d[54]), "+f"(d[55]),
          "+f"(d[56]), "+f"(d[57]), "+f"(d[58]), "+f"(d[59]), "+f"(d[60]), "+f"(d[61]), "+f"(d[62]), "+f"(d[63]),
          "+f"(d[64]), "+f"(d[65]), "+f"(d[66]), "+f"(d[67]), "+f"(d[68]), "+f"(d[69]), "+f"(d[70]), "+f"(d[71]),
          "+f"(d[72]), "+f"(d[73]), "+f"(d[74]), "+f"(d[75]), "+f"(d[76]), "+f"(d[77]), "+f"(d[78]), "+f"(d[79]),
          "+f"(d[80]), "+f"(d[81]), "+f"(d[82]), "+f"(d[83]), "+f"(d[84]), "+f"(d[85]), "+f"(d[86]), "+f"(d[87]),
          "+f"(d[88]), "+f"(d[89]), "+f"(d[90]), "+f"(d[91]), "+f"(d[92]), "+f"(d[93]), "+f"(d[94]), "+f"(d[95])
        : "r"(a0), "r"(a1), "r"(a2), "r"(a3), "r"(blo), "r"(bhi));
}
__device__ __forceinline__ void mma_ss_n64(float (&d)[32], uint32_t alo, uint32_t ahi, uint32_t blo, uint32_t bhi) {
    asm volatile("{\n.reg .b64 da, db;\nmov.b64 da, {%32, %33};\nmov.b64 db, {%34, %35};\n"
        "wgmma.mma_async.sync.aligned.m64n64k16.f32.bf16.bf16 "
        "{%0, %1, %2, %3, %4, %5, %6, %7, %8, %9, %10, %11, %12, %13, %14, %15, "
        "%16, %17, %18, %19, %20, %21, %22, %23, %24, %25, %26, %27, %28, %29, %30, %31}, "
        "da, db, 1, 1, 1, 0, 1;\n}\n"
        : "+f"(d[0]), "+f"(d[1]), "+f"(d[2]), "+f"(d[3]), "+f"(d[4]), "+f"(d[5]), "+f"(d[6]), "+f"(d[7]),
          "+f"(d[8]), "+f"(d[9]), "+f"(d[10]), "+f"(d[11]), "+f"(d[12]), "+f"(d[13]), "+f"(d[14]), "+f"(d[15]),
          "+f"(d[16]), "+f"(d[17]), "+f"(d[18]), "+f"(d[19]), "+f"(d[20]), "+f"(d[21]), "+f"(d[22]), "+f"(d[23]),
          "+f"(d[24]), "+f"(d[25]), "+f"(d[26]), "+f"(d[27]), "+f"(d[28]), "+f"(d[29]), "+f"(d[30]), "+f"(d[31])
        : "r"(alo), "r"(ahi), "r"(blo), "r"(bhi));
}
__device__ __forceinline__ void mma_rs_n72(float (&d)[36], uint32_t a0, uint32_t a1, uint32_t a2, uint32_t a3, uint32_t blo, uint32_t bhi) {
    asm volatile("{\n.reg .b64 da, db;\nmov.b64 db, {%40, %41};\n"
        "wgmma.mma_async.sync.aligned.m64n72k16.f32.bf16.bf16 "
        "{%0, %1, %2, %3, %4, %5, %6, %7, %8, %9, %10, %11, %12, %13, %14, %15, "
        "%16, %17, %18, %19, %20, %21, %22, %23, %24, %25, %26, %27, %28, %29, %30, %31, "
        "%32, %33, %34, %35}, "
        "{%36, %37, %38, %39}, db, 1, 1, 1, 1;\n}\n"
        : "+f"(d[0]), "+f"(d[1]), "+f"(d[2]), "+f"(d[3]), "+f"(d[4]), "+f"(d[5]), "+f"(d[6]), "+f"(d[7]),
          "+f"(d[8]), "+f"(d[9]), "+f"(d[10]), "+f"(d[11]), "+f"(d[12]), "+f"(d[13]), "+f"(d[14]), "+f"(d[15]),
          "+f"(d[16]), "+f"(d[17]), "+f"(d[18]), "+f"(d[19]), "+f"(d[20]), "+f"(d[21]), "+f"(d[22]), "+f"(d[23]),
          "+f"(d[24]), "+f"(d[25]), "+f"(d[26]), "+f"(d[27]), "+f"(d[28]), "+f"(d[29]), "+f"(d[30]), "+f"(d[31]),
          "+f"(d[32]), "+f"(d[33]), "+f"(d[34]), "+f"(d[35])
        : "r"(a0), "r"(a1), "r"(a2), "r"(a3), "r"(blo), "r"(bhi));
}

constexpr int A_STAGES = 11;
constexpr uint32_t A_STAGE_BYTES = 14336;
constexpr uint32_t A_OFF_X = A_STAGES * A_STAGE_BYTES;
constexpr uint32_t A_OFF_STG = 7 * A_STAGE_BYTES;
constexpr uint32_t A_OFF_MISC = A_OFF_X + 4 * 16384;
constexpr uint32_t A_SMEM = A_OFF_MISC + 512 + 2048 + 256 + 1024;
__device__ __forceinline__ uint32_t x_slot(int kc) { return A_OFF_X + ((kc + 3) & 3) * 16384; }

__device__ __forceinline__ uint32_t absmax_bf16x2(uint32_t m, uint32_t a) {
    uint32_t r;
    asm volatile("max.xorsign.abs.bf16x2 %0, %1, %2;" : "=r"(r) : "r"(m), "r"(a));
    return r;
}

__device__ __forceinline__ void qkv_addr(uint32_t (&addr)[9], uint32_t sb, bool isv, int warp, int lane) {
#pragma unroll
    for (int j = 0; j < 9; j++) {
        const int c = 8 * j + 2 * (lane & 3), slot = c / 18, d0 = c - slot * 18;
        const int d = isv && d0 < 16 ? ((d0 & 2) << 2) | ((d0 >> 2) << 1) : d0;
        addr[j] = sb + (lane >> 2) * 16 + warp * 2 * (isv ? 384u : 128u) + slot * BLK_BYTES + (d & 7) * 2 + (d >> 3) * (isv ? 128u : 2048u);
    }
}
template <int ODD>
__device__ __forceinline__ void qkv_epilogue(const float (&acc)[112], uint32_t (&addr)[9], uint32_t sb, uint32_t s_cs, uint32_t bar_out, float2 st0, float2 st1,
                                             int ct, int rb, int warp, int lane) {
    const int t = lane & 3;
    uint32_t w[54], vmax = 0;
#pragma unroll
    for (int p = 0; p < 3; p++) {
        float2 cs[9];
#pragma unroll
        for (int j = 0; j < 9; j++) cs[j] = lds64f(s_cs + 32 * (9 * p + j + ODD) + 8 * t);
        if (p == 1 && ct == 5) qkv_addr(addr, sb, true, warp, lane);
        const uint32_t gs = ct * 3 + p >= 16 ? 384u : 128u;
        const float sc = ct * 3 + p < 8 ? QSCALE : 1.f;
        const float f0 = st0.y * sc, f1 = st1.y * sc;
#pragma unroll
        for (int j = 0; j < 9; j++) {
            const float* a = &acc[4 * (9 * p + j + ODD)];
            w[18 * p + 2 * j] = pack_bf16((a[0] - st0.x * cs[j].x) * f0, (a[1] - st0.x * cs[j].y) * f0);
            w[18 * p + 2 * j + 1] = pack_bf16((a[2] - st1.x * cs[j].x) * f1, (a[3] - st1.x * cs[j].y) * f1);
            sts32(addr[j] + p * 4 * BLK_BYTES, w[18 * p + 2 * j]);
            sts32(addr[j] + gs + p * 4 * BLK_BYTES, w[18 * p + 2 * j + 1]);
        }
        fence_async_smem();
        __syncwarp();
        if (lane == 0) mbar_arrive(bar_out + 8 * p);
    }
    if (ct < 2) return;
#pragma unroll
    for (int i = 0; i < 54; i++) vmax = absmax_bf16x2(vmax, w[i]);
    float m = fmaxf(fabsf(bf_lo(vmax)), fabsf(bf_hi(vmax)));
#pragma unroll
    for (int o = 16; o > 0; o >>= 1) m = fmaxf(m, __shfl_xor_sync(~0u, m, o));
    if (lane == 0) g_kmax[ct * 128 + rb * 8 + warp] = m;
}

__global__ void __launch_bounds__(384, 1)
qkv_kernel(const __grid_constant__ CUtensorMap tm_x, const __grid_constant__ CUtensorMap tm_w, const __nv_bfloat16* __restrict__ x) {
    extern __shared__ uint8_t smem_raw[];
    uint32_t spins = 0;
    const int tid = threadIdx.x, warp = __shfl_sync(~0u, tid >> 5, 0), lane = tid & 31;
    pdl_launch();
    const uint32_t sb = (smem_u32(smem_raw) + 1023u) & ~1023u;
    const uint32_t bar_a = sb + A_OFF_MISC, bar_full = bar_a + 72, bar_empty = bar_full + 96, bar_xfree = bar_empty + 56;
    const uint32_t bar_dead = bar_xfree + 40, bar_out = bar_dead + 8;
    const uint32_t s_cs = sb + A_OFF_MISC + 512, s_st = s_cs + 1024, s_red = s_st + 1024;
    const int rb = blockIdx.x & 15, ct = blockIdx.x >> 4;
    const uint32_t rank = blockIdx.x & 1;
    const int col0 = 216 * ct - 8 * (ct & 1);
    const int krot = rb >> 1;

    if (lane == 0) {
        mbar_init(bar_a + 8 * warp, 1);
        const int es = warp >= 9 ? warp - 9 : warp + 3, a0 = (8 * krot) >> 5, a1 = (8 * krot + 36) >> 5;
        const uint32_t ecnt = 4 + (es == a0 || es == a0 + 1) + (es == a1 || es == a1 + 1);
        mbar_init(bar_a + 8 * (warp + 12), warp < 9 ? 1 : ecnt);
        if (warp < 10) mbar_init(bar_a + 8 * (warp + 24), warp < 4 ? ecnt : 2);
        if (warp >= 2 && warp < 5) mbar_init(bar_out + 8 * (warp - 2), 8);
        fence_mbar_init();
        if (warp == 0) {
            mbar_expect(bar_a, 16384);
            tma_2d(sb + x_slot(0), &tm_x, krot * 64, rb * 128, bar_a);
        }
        if (warp == 1) tma_prefetch_desc(&tm_w);
    }
    __syncwarp();
    cluster_sync();
    if (lane == 0) {
        if (warp < 4) {
            mbar_expect(bar_full + 8 * warp, A_STAGE_BYTES);
            tma_3d_mc(sb + warp * A_STAGE_BYTES + rank * 7168, &tm_w, col0, krot * 64 + warp * 32 + rank * 16, bar_full + 8 * warp);
        } else if (warp == 4) {
            mbar_expect(bar_a + 8, 16384);
            tma_2d(sb + x_slot(1), &tm_x, krot * 64 + 64, rb * 128, bar_a + 8);
        }
    }
    __syncwarp();

    if (warp == 8) {
        if (lane == 0) {
#pragma unroll 1
            for (int s = 4; s < 20; s++) {
                if (s < 7 ? !(s & 1) : (s > 10 && (s & 1))) {
                    const int kc = s < 7 ? s >> 1 : (s >> 1) - 1;
                    if (kc >= 4) mbar_wait_trap(bar_xfree + 8 * (kc - 4), 0);
                    mbar_expect(bar_a + 8 * kc, 16384);
                    tma_2d(sb + x_slot(kc), &tm_x, (krot + kc >= 9 ? krot + kc - 9 : krot + kc) * 64, rb * 128, bar_a + 8 * kc);
                }
                if (s < 18) {
                    const int slot = s >= A_STAGES ? s - A_STAGES : s;
                    if (s >= A_STAGES) mbar_wait_trap(bar_empty + 8 * slot, 0);
                    int k = krot * 64 + s * 32;
                    if (k >= DM) k -= DM;
                    mbar_expect(bar_full + 8 * slot, A_STAGE_BYTES);
                    tma_3d_mc(sb + slot * A_STAGE_BYTES + rank * 7168, &tm_w, col0, k + rank * 16, bar_full + 8 * slot);
                }
            }
        }
        __syncwarp();
        if (lane < 4) {
#pragma unroll 1
            for (int p = 0; p < 3; p++) {
                mbar_wait_trap(bar_out + 8 * p, 0);
                bulk_store(g_qkv + (size_t)(ct * 12 + 4 * p + lane) * SLOT_BYTES + rb * BLK_BYTES, sb + A_OFF_STG + (4 * p + lane) * BLK_BYTES, BLK_BYTES);
                bulk_commit();
            }
            bulk_wait_all();
        }
    } else if (warp > 8) {
        if (warp == 9) {
            const int u = (lane < 27 ? lane : 0) + (ct & 1), r0 = 8 * krot + 36 * rank;
            {
                uint4 v[36];
                uint32_t seen = 0;
                mbar_wait_trap(bar_full + 8 * (r0 >> 5), 0);
                mbar_wait_trap(bar_full + 8 * (r0 >> 5) + 8, 0);
#pragma unroll
                for (int k = 0; k < 36; k++) {
                    const int r = r0 + (k & ~3);
                    v[k] = lds128(sb + (r >> 4) * 7168 + ((r & 15) + (k & 3)) * 64 + (u >> 2) * 1024 + (((u & 3) ^ (((r + (k & 3)) >> 1) & 3)) << 4));
                    seen |= v[k].x;
                }
                sts32(s_red + lane * 4, seen);
                __syncwarp();
                if (lane < 4) mbar_arrive_cluster(mapa(bar_empty + 8 * ((r0 >> 5) + (lane >> 1)), lane & 1));
                float c0 = 0.f, c1 = 0.f;
#pragma unroll
                for (int j = 0; j < 4; j++) {
                    c0 *= 0.f; c1 *= 0.f;
#pragma unroll
                    for (int k = 0; k < 36; k++) {
                        const uint32_t w = j == 0 ? v[k].x : j == 1 ? v[k].y : j == 2 ? v[k].z : v[k].w;
                        c0 += bf_lo(w); c1 += bf_hi(w);
                    }
                    if (lane < 27) st_strong(&g_cs0[(ct * 16 + rb) * 216 + lane * 8 + j * 2], __float_as_uint(c0) | 1u, __float_as_uint(c1) | 1u);
                }
            }
            if (lane < 12 && blockIdx.x * 12 + lane < N_FLAG_C) g_flag_c[blockIdx.x * 12 + lane] = 0;
#pragma unroll 1
            for (uint32_t it = 0; flag_poll((const unsigned int*)&g_cs0[(ct * 16 + (lane & 15)) * 216 + 215], true, 1) != ~0u; it++)
                if (it > SPIN_LIMIT) __trap();
            if (lane < 27) {
                uint4 v[32];
#pragma unroll 1
                for (uint32_t it = 0;; it++) {
                    bool ok = true;
#pragma unroll
                    for (int i = 0; i < 32; i++) {
                        v[i] = ld_strong(&g_cs0[(ct * 16 + (i >> 1)) * 216 + lane * 8 + (i & 1) * 4]);
                        ok = ok && v[i].x && v[i].y && v[i].z && v[i].w;
                    }
                    if (ok) break;
                    if (it > SPIN_LIMIT) __trap();
                }
#pragma unroll
                for (int hh = 0; hh < 2; hh++) {
                    float a = 0.f, b = 0.f, c = 0.f, d = 0.f;
#pragma unroll
                    for (int i = hh; i < 32; i += 2) { a += __uint_as_float(v[i].x); b += __uint_as_float(v[i].y); c += __uint_as_float(v[i].z); d += __uint_as_float(v[i].w); }
                    sts128(s_cs + 32 * (ct & 1) + lane * 32 + hh * 16, __float_as_uint(a), __float_as_uint(b), __float_as_uint(c), __float_as_uint(d));
                }
            }
        } else {
            const int row = tid - 320, rl = row >> 2;
            mbar_wait_trap(bar_a, 0);
            const uint4* px = (const uint4*)(x + (size_t)(rb * 128 + ct * 16 + rl) * DM) + (lane & 3);
            uint4 v[18];
#pragma unroll
            for (int i = 0; i < 18; i++) v[i] = __ldg(px + 4 * i);
            float sum = 0.f, sq = 0.f;
#pragma unroll
            for (int i = 0; i < 18; i++) {
                sum += bf_lo(v[i].x); sum += bf_hi(v[i].x); sum += bf_lo(v[i].y); sum += bf_hi(v[i].y);
                sum += bf_lo(v[i].z); sum += bf_hi(v[i].z); sum += bf_lo(v[i].w); sum += bf_hi(v[i].w);
            }
            sum += __shfl_xor_sync(~0u, sum, 1); sum += __shfl_xor_sync(~0u, sum, 2);
            const float mean = sum * (1.f / DM);
#pragma unroll
            for (int i = 0; i < 18; i++) {
                const uint32_t w[4] = {v[i].x, v[i].y, v[i].z, v[i].w};
#pragma unroll
                for (int k = 0; k < 4; k++) { const float a = bf_lo(w[k]) - mean, b = bf_hi(w[k]) - mean; sq = fmaf(a, a, sq); sq = fmaf(b, b, sq); }
            }
            sq += __shfl_xor_sync(~0u, sq, 1); sq += __shfl_xor_sync(~0u, sq, 2);
            if ((lane & 3) == 0) st_strong(&g_xstat[rb * 128 + ct * 16 + rl], __float_as_uint(mean) | 1u, __float_as_uint(rsqrtf(sq * (1.f / DM) + LN_EPS)) | 1u);
#pragma unroll 1
            for (uint32_t it = 0;; it++) {
                const uint4 w = ld_strong(&g_xstat[rb * 128 + row * 2]);
                if (w.x && w.y && w.z && w.w) { sts128(s_st + row * 16, w.x, w.y, w.z, w.w); break; }
                if (it > SPIN_LIMIT) __trap();
            }
            __syncwarp();
            mbar_wait_trap(bar_dead, 0);
            const uint32_t sel0 = ((POLY_PATTERN >> (row >> 3)) & 1) ? 0x3F803F80u : 0u, sel1 = ((POLY_PATTERN >> ((row >> 3) + 8)) & 1) ? 0x3F803F80u : 0u;
#pragma unroll 1
            for (int p = 0; p < 3; p++) {
                const int kind = (ct * 3 + p) >> 3;
                const uint32_t gs = kind == 2 ? 384u : 128u;
                const uint32_t a = sb + A_OFF_STG + p * 4 * BLK_BYTES + (row & 7) * 16 + (row >> 3) * gs + (kind == 2 ? 256u : 4096u);
                const uint32_t w0 = kind == 0 ? 0x42FE47C0u : kind == 2 ? 0x00003F80u : sel0, w1 = kind == 1 ? sel1 : w0;
#pragma unroll
                for (int i = 0; i < 4; i++) {
                    sts32(a + i * BLK_BYTES + 4, w0); sts64f(a + i * BLK_BYTES + 8, 0.f, 0.f);
                    sts32(a + i * BLK_BYTES + 8 * gs + 4, w1); sts64f(a + i * BLK_BYTES + 8 * gs + 8, 0.f, 0.f);
                }
            }
            fence_async_smem();
        }
        __syncwarp();
        nbar_arrive(2, 352);
    } else {
        const int wg = warp >> 2;
        float acc[112];
#pragma unroll
        for (int i = 0; i < 112; i++) acc[i] = 0.f;
        const uint32_t a_lo = desc_addr(sb + wg * 8192) | (1u << 16);
        const uint32_t b_lo = desc_addr(sb) | ((1024 >> 4) << 16);
        const uint32_t rel = (tid & 127) == 0 ? bar_empty : mapa(bar_empty, rank ^ 1);
        const bool do_rel = (tid & 95) == 0;
        uint32_t addr[9];
        qkv_addr(addr, sb + A_OFF_STG, ct >= 6, warp, lane);
        fence_regs(addr);
#pragma unroll 1
        for (int s = 0; s < 18; s++) {
            const int slot = s >= A_STAGES ? s - A_STAGES : s;
            if (!(s & 1)) mbar_wait(bar_a + 4 * s, 0, spins);
            mbar_wait(bar_full + 8 * slot, s >= A_STAGES, spins);
            const uint32_t al = a_lo + (x_slot(s >> 1) >> 4) + (s & 1) * 4, bl = b_lo + slot * (A_STAGE_BYTES >> 4);
            wg_fence();
            mma_ss_n224(acc, al, HI_SW128, bl, HI_SW64, 1);
            mma_ss_n224(acc, al + 2, HI_SW128, bl + (7168 >> 4), HI_SW64, 1);
            wg_commit();
            wg_wait<1>();
            if (do_rel && s >= 1 && s <= 18 - A_STAGES) mbar_arrive_cluster(rel + 8 * (s - 1));
            if ((tid & 127) == 64) {
                if (s >= 2 && s <= 10 && !(s & 1)) mbar_arrive(bar_xfree + 4 * (s - 2));
                if (s == 12) mbar_arrive(bar_dead);
            }
        }
        wg_wait<0>();
        fence_regs(acc);
        nbar_sync(2, 352);
        const float2 st0 = lds64f(s_st + (warp * 16 + (lane >> 2)) * 8), st1 = lds64f(s_st + (warp * 16 + 8 + (lane >> 2)) * 8);
        if (ct & 1) qkv_epilogue<1>(acc, addr, sb + A_OFF_STG, s_cs, bar_out, st0, st1, ct, rb, warp, lane);
        else qkv_epilogue<0>(acc, addr, sb + A_OFF_STG, s_cs, bar_out, st0, st1, ct, rb, warp, lane);
    }
}

constexpr uint32_t B_OFF_Q = 2 * SLOT_BYTES, B_OFF_KMAX = B_OFF_Q + 4 * BLK_BYTES, B_OFF_BAR = B_OFF_KMAX + 1024;
constexpr uint32_t B_SMEM = B_OFF_BAR + 64;
constexpr uint32_t QK_LBO = (2048 >> 4) << 16, V_LBO = (384 >> 4) << 16, HI_NOSW = 128 >> 4;

__device__ __forceinline__ uint32_t exp_pair_poly(float a, float b, uint32_t c_or, uint32_t c_mul) {
    const uint32_t u = __byte_perm(__float_as_uint(a), __float_as_uint(b), 0x5410);
    uint32_t g, w, p, r;
    asm("lop3.b32 %0, %1, 0x007F007F, %2, 0xEA;" : "=r"(g) : "r"(u), "r"(c_or));
    asm("fma.rn.f16x2 %0, %1, %2, %3;" : "=r"(w) : "r"(g), "r"(c_mul), "r"(0xC40EC40Eu));
    asm("fma.rn.f16x2 %0, %1, %1, %2;" : "=r"(p) : "r"(w), "r"(0x47AE47AEu));
    asm("lop3.b32 %0, %1, %2, 0x007F007F, 0xD8;" : "=r"(r) : "r"(u), "r"(p));
    return r;
}
template <int JOFF>
__device__ __forceinline__ void exp_tile(const float (&s)[32], uint32_t (&p)[16], uint32_t c_or, uint32_t c_mul) {
#pragma unroll
    for (int j = 0; j < 8; j++) {
        if ((POLY_PATTERN >> (j + JOFF)) & 1) {
            p[2 * j] = exp_pair_poly(s[4 * j], s[4 * j + 1], c_or, c_mul);
            p[2 * j + 1] = exp_pair_poly(s[4 * j + 2], s[4 * j + 3], c_or, c_mul);
        } else {
            p[2 * j] = pack_bf16(ex2(s[4 * j]), ex2(s[4 * j + 1]));
            p[2 * j + 1] = pack_bf16(ex2(s[4 * j + 2]), ex2(s[4 * j + 3]));
        }
    }
}
__device__ __forceinline__ void qk_tile(float (&s)[32], const uint32_t (&q)[8], uint64_t k) {
    mma_qk_first(s, q[0], q[1], q[2], q[3], k + QK_LBO);
    mma_qk_second(s, q[4], q[5], q[6], q[7], k + 256);
}
__device__ __forceinline__ void pv_tile(float (&o)[12], const uint32_t (&p)[16], uint64_t v) {
#pragma unroll
    for (int kk = 0; kk < 4; kk++) mma_pv(o, p[4 * kk], p[4 * kk + 1], p[4 * kk + 2], p[4 * kk + 3], v + kk * 48);
}
__device__ __forceinline__ void load_q(uint32_t (&q)[8], uint32_t sq) {
    q[0] = lds32(sq); q[1] = lds32(sq + 128); q[2] = lds32(sq + 2048); q[3] = lds32(sq + 2176);
    q[4] = lds32(sq + 4096); q[5] = lds32(sq + 4224); q[6] = lds32((sq + 4096) | 12); q[7] = lds32((sq + 4224) | 12);
}
__device__ __forceinline__ float q_l1(const uint32_t (&q)[8], int lane) {
    const bool first = (lane & 3) == 0;
    float n0 = fabsf(bf_lo(q[0])) + fabsf(bf_hi(q[0])) + fabsf(bf_lo(q[2])) + fabsf(bf_hi(q[2])) + (first ? fabsf(bf_lo(q[4])) + fabsf(bf_hi(q[4])) : 0.f);
    float n1 = fabsf(bf_lo(q[1])) + fabsf(bf_hi(q[1])) + fabsf(bf_lo(q[3])) + fabsf(bf_hi(q[3])) + (first ? fabsf(bf_lo(q[5])) + fabsf(bf_hi(q[5])) : 0.f);
    n0 += __shfl_xor_sync(~0u, n0, 1); n1 += __shfl_xor_sync(~0u, n1, 1);
    n0 += __shfl_xor_sync(~0u, n0, 2); n1 += __shfl_xor_sync(~0u, n1, 2);
    return n0 > n1 || n0 != n0 ? n0 : n1;
}
__device__ __forceinline__ void stage_attn(const float (&o)[12], uint32_t stg, int h, int tid) {
    const int lane = tid & 31;
    const float r0 = __fdividef(1.f, __shfl_sync(~0u, o[8], (lane & ~3) | 1)), r1 = __fdividef(1.f, __shfl_sync(~0u, o[10], (lane & ~3) | 1));
    const uint32_t a = stg + ((tid >> 6) & 1) * 2048 + ((tid >> 5) & 1) * 512 + lane * 8;
    sts64f(a, __uint_as_float(pack_bf16(o[0] * r0, o[1] * r0)), __uint_as_float(pack_bf16(o[4] * r0, o[5] * r0)));
    sts64f(a + 256, __uint_as_float(pack_bf16(o[2] * r1, o[3] * r1)), __uint_as_float(pack_bf16(o[6] * r1, o[7] * r1)));
    if ((lane & 3) == 0) {
        const uint32_t b = ((tid >> 5) & 3) * 64 + (h & 3) * 32 + lane;
        sts32(stg + 4096 + (b & 255), pack_bf16(o[8] * r0, o[9] * r0));
        sts32(stg + 4096 + ((b + 32) & 255), pack_bf16(o[10] * r1, o[11] * r1));
    }
}
__device__ __forceinline__ bool wg_any(bool pred, uint32_t id) {
    uint32_t r;
    asm volatile("{\n.reg .pred p, q;\nsetp.ne.u32 p, %1, 0;\nbar.red.or.pred q, %2, 128, p;\nselp.u32 %0, 1, 0, q;\n}\n" : "=r"(r) : "r"((uint32_t)pred), "r"(id) : "memory");
    return __any_sync(~0u, r);
}
__device__ __forceinline__ void attn_safe_block(uint64_t k0, uint32_t (&q)[8], float (&o)[12]) {
    if (threadIdx.x & 3) { q[4] = 0; q[5] = 0; }
    float s[32], m0 = -INFINITY, m1 = -INFINITY;
    uint32_t p[16];
#pragma unroll
    for (int i = 0; i < 12; i++) o[i] = 0.f;
#pragma unroll 1
    for (int i = 0; i < 32; i++) {
        wg_fence();
        qk_tile(s, q, k0 + (i >> 1) * 384 + (i & 1) * 64);
        wg_commit();
        wg_wait<0>();
        fence_regs(s);
        float n0 = m0, n1 = m1;
#pragma unroll
        for (int j = 0; j < 8; j++) { n0 = fmaxf(n0, fmaxf(s[4 * j], s[4 * j + 1])); n1 = fmaxf(n1, fmaxf(s[4 * j + 2], s[4 * j + 3])); }
        n0 = fmaxf(n0, __shfl_xor_sync(~0u, n0, 1)); n0 = fmaxf(n0, __shfl_xor_sync(~0u, n0, 2));
        n1 = fmaxf(n1, __shfl_xor_sync(~0u, n1, 1)); n1 = fmaxf(n1, __shfl_xor_sync(~0u, n1, 2));
        const float c0 = ex2(m0 - n0), c1 = ex2(m1 - n1);
        m0 = n0; m1 = n1;
#pragma unroll
        for (int j = 0; j < 3; j++) { o[4 * j] *= c0; o[4 * j + 1] *= c0; o[4 * j + 2] *= c1; o[4 * j + 3] *= c1; }
#pragma unroll
        for (int j = 0; j < 8; j++) {
            p[2 * j] = pack_bf16(ex2(s[4 * j] - m0), ex2(s[4 * j + 1] - m0));
            p[2 * j + 1] = pack_bf16(ex2(s[4 * j + 2] - m1), ex2(s[4 * j + 3] - m1));
        }
        fence_regs(o);
        wg_fence();
        pv_tile(o, p, k0 + (SLOT_BYTES >> 4) + V_LBO + i * 192);
        wg_commit();
        wg_wait<0>();
        fence_regs(o);
    }
}

__global__ void __launch_bounds__(512, 1)
attn_kernel(const __grid_constant__ CUtensorMap tm_wo, const __grid_constant__ CUtensorMap tm_wo2, const __grid_constant__ CUtensorMap tm_ast,
            const __nv_bfloat16* __restrict__ w1) {
    extern __shared__ __align__(128) uint8_t smem_raw[];
    uint32_t spins = 0;
    const int tid = threadIdx.x, lane = tid & 31;
    const uint32_t sk = smem_u32(smem_raw), sv = sk + SLOT_BYTES, bar = sk + B_OFF_BAR;
    if (blockIdx.x < 4) {
        if (tid == 480) {
            mbar_init(bar, 1);
            fence_mbar_init();
            fence_async_smem();
            mbar_expect(bar, 2 * 82944);
#pragma unroll 1
            for (int i = 0; i < 4; i++)
                asm volatile("cp.async.bulk.tensor.4d.shared::cluster.global.mbarrier::complete_tx::bytes [%0], [%1, {%3, %4, %4, %5}], [%2];"
                             :: "r"(sk + 16384 + (i >> 1) * 82944 + (i & 1) * 36864), "l"(&tm_wo), "r"(bar), "r"((blockIdx.x * 2 + (i >> 1)) * 72), "r"(0), "r"((i & 1) * 16) : "memory");
#pragma unroll 1
            for (int i = 0; i < 2; i++)
                asm volatile("cp.async.bulk.tensor.5d.shared::cluster.global.mbarrier::complete_tx::bytes [%0], [%1, {%3, %4, %4, %4, %4}], [%2];"
                             :: "r"(sk + 16384 + i * 82944 + 73728), "l"(&tm_wo2), "r"(bar), "r"((blockIdx.x * 2 + i) * 72), "r"(0) : "memory");
            mbar_wait(bar, 0, spins);
            bulk_store(g_wo_img + blockIdx.x * 2 * 82944, sk + 16384, 2 * 82944);
            bulk_commit();
            bulk_wait_all();
            asm volatile("fence.proxy.async.global;\nfence.release.gpu;" ::: "memory");
            pdl_launch();
        }
        float* red = (float*)smem_raw;
        const int cg = tid % 144, part = tid / 144;
        float c[8] = {0.f, 0.f, 0.f, 0.f, 0.f, 0.f, 0.f, 0.f};
        if (part < 3) {
            const uint4* pw = (const uint4*)(w1 + (size_t)part * 192 * FF + blockIdx.x * 1152) + cg;
#pragma unroll 16
            for (int k = 0; k < 192; k++) {
                const uint4 v = __ldg(pw + (size_t)k * (FF / 8));
                c[0] += bf_lo(v.x); c[1] += bf_hi(v.x); c[2] += bf_lo(v.y); c[3] += bf_hi(v.y);
                c[4] += bf_lo(v.z); c[5] += bf_hi(v.z); c[6] += bf_lo(v.w); c[7] += bf_hi(v.w);
            }
#pragma unroll
            for (int k = 0; k < 8; k++) red[part * 1152 + cg * 8 + k] = c[k];
        }
        __syncthreads();
        for (int i = tid; i < 144 * 8; i += 512) {
            const int core = i >> 3, k = i & 7;
            uint32_t w[4] = {0u, 0u, 0u, 0u};
            if (k < 3) {
#pragma unroll
                for (int j = 0; j < 4; j++) {
                    const int c0 = core * 8 + 2 * j;
                    const float a = -(red[c0] + red[1152 + c0] + red[2304 + c0]), b = -(red[c0 + 1] + red[1153 + c0] + red[2305 + c0]);
                    const uint32_t hi = pack_bf16(a, b);
                    w[j] = k == 1 ? pack_bf16(a - bf_lo(hi), b - bf_hi(hi)) : hi;
                }
            }
            ((uint4*)g_cs1)[blockIdx.x * 1152 + i] = make_uint4(w[0], w[1], w[2], w[3]);
        }
        return;
    }
    const int h = (blockIdx.x - 4) >> 2, qt = blockIdx.x & 3;
    if (lane == 0 && tid < 96) {
        mbar_init(bar + (tid >> 2), 1);
        fence_mbar_init();
    }
    if (tid == 192) tma_prefetch_desc(&tm_ast);
    if (tid == 160) { sts32(bar + 40, 0x48004800u); sts32(bar + 44, 0x38A038A0u); }
    __syncthreads();
    const uint32_t c_or = lds32(bar + 40), c_mul = lds32(bar + 44);
    {
        const int w = tid >> 7;
        const uint8_t* src = g_qkv + (size_t)((w & 1) * (16 + 16 * w) + h) * SLOT_BYTES + ((w & 1) ? 0 : (qt * 4 + w) * BLK_BYTES);
        const uint32_t dst = (w & 1) ? sk + (w >> 1) * SLOT_BYTES : sk + B_OFF_Q + w * BLK_BYTES;
        uint32_t bytes = (w & 1) ? BLK_BYTES : 2 * BLK_BYTES;
        if (tid == 0) mbar_expect(bar, 6 * BLK_BYTES);
        asm volatile("" : "+l"(src), "+r"(bytes) :: "memory");
        pdl_wait();
        if ((tid & 127) == 0) bulk_load(dst, src, bytes, bar);
        pdl_launch();
        if (tid < 8) ((uint4*)g_xstat)[(blockIdx.x - 4) * 8 + tid] = make_uint4(0, 0, 0, 0);
        else if (tid < 62) ((uint4*)g_cs0)[(blockIdx.x - 4) * 54 + tid - 8] = make_uint4(0, 0, 0, 0);
    }
    const uint8_t* gk = g_qkv + (size_t)(32 + h) * SLOT_BYTES;
    auto load_kv = [&](uint32_t off, uint32_t bytes, uint32_t b) {
        bulk_load(sk + off, gk + off, bytes, b);
        bulk_load(sv + off, gk + 32 * SLOT_BYTES + off, bytes, b);
    };
    const uint64_t k0 = desc_addr(sk) | ((uint64_t)HI_NOSW << 32);
    const uint32_t sq = sk + B_OFF_Q + (tid >> 8) * BLK_BYTES + ((tid >> 5) & 7) * 256 + lane * 4;
    float oa[12], ob[12];
#pragma unroll
    for (int i = 0; i < 12; i++) { oa[i] = 0.f; ob[i] = 0.f; }
    mbar_wait(bar, 0, spins);
    uint32_t qa[8], qb[8];
    load_q(qa, sq);
    load_q(qb, sq + 2 * BLK_BYTES);
    fence_regs(oa); fence_regs(ob); fence_regs(qa); fence_regs(qb);
    {
        float s[32]; uint32_t p[16];
        uint64_t k = k0;
#pragma unroll 1
        for (int seg = 0; seg < 3; seg++) {
            mbar_wait(bar + 8 * seg, 0, spins);
            if (seg == 0 && tid == 256) { mbar_expect(bar + 8, 6 * BLK_BYTES); load_kv(BLK_BYTES, 3 * BLK_BYTES, bar + 8); }
            if (seg == 1 && tid == 384) {
                mbar_expect(bar + 16, 24 * BLK_BYTES + 1024);
                load_kv(4 * BLK_BYTES, 12 * BLK_BYTES, bar + 16);
                bulk_load(sk + B_OFF_KMAX, g_kmax + ((32 + h) / 12) * 128, 512, bar + 16);
                bulk_load(sk + B_OFF_KMAX + 512, g_kmax + ((64 + h) / 12) * 128, 512, bar + 16);
            }
            __syncwarp();
            const int nblk = seg == 0 ? 1 : seg == 1 ? 3 : 12;
#pragma unroll 1
            for (int b = 0; b < nblk; b++, k += 384) {
                const uint64_t v = k + (SLOT_BYTES >> 4) + V_LBO;
                wg_fence();
                qk_tile(s, qa, k);
                wg_commit();
                wg_wait<0>();
                fence_regs(s); fence_regs(p);
                exp_tile<0>(s, p, c_or, c_mul);
                wg_fence();
                pv_tile(oa, p, v);
                qk_tile(s, qb, k);
                wg_commit();
                wg_wait<0>();
                fence_regs(s); fence_regs(p);
                exp_tile<0>(s, p, c_or, c_mul);
                wg_fence();
                pv_tile(ob, p, v);
                qk_tile(s, qa, k + 64);
                wg_commit();
                wg_wait<0>();
                fence_regs(s); fence_regs(p);
                exp_tile<8>(s, p, c_or, c_mul);
                wg_fence();
                pv_tile(oa, p, v + 192);
                qk_tile(s, qb, k + 64);
                wg_commit();
                wg_wait<0>();
                fence_regs(s); fence_regs(p);
                exp_tile<8>(s, p, c_or, c_mul);
                wg_fence();
                pv_tile(ob, p, v + 192);
                wg_commit();
            }
        }
    }
    const uint4 km = lds128(sk + B_OFF_KMAX + lane * 16), vm = lds128(sk + B_OFF_KMAX + 512 + lane * 16);
    const float kmax = __uint_as_float(__reduce_max_sync(~0u, max(max(km.x, km.y), max(km.z, km.w))));
    const float vmax = __uint_as_float(__reduce_max_sync(~0u, max(max(vm.x, vm.y), max(vm.z, vm.w))));
    const bool unsafe = wg_any(!(fmaxf(q_l1(qa, lane), q_l1(qb, lane)) * kmax <= 100.f && vmax <= 32768.f), 1 + (tid >> 7));
    wg_wait<0>();
    fence_regs(oa); fence_regs(ob);
    const uint32_t stg = sk + B_OFF_Q + (tid >> 8) * BLK_BYTES + ((tid >> 7) & 1) * 1024;
    if (!unsafe) {
        stage_attn(oa, stg, h, tid);
        stage_attn(ob, stg + 2 * BLK_BYTES, h, tid);
    } else {
#pragma unroll 1
        for (int u = 0; u < 2; u++) {
            load_q(qa, sq + u * 2 * BLK_BYTES);
            attn_safe_block(k0, qa, oa);
            stage_attn(oa, stg + u * 2 * BLK_BYTES, h, tid);
        }
    }
    fence_async_smem();
    nbar_sync(1 + (tid >> 7), 128);
    if (lane == 0) {
        const int w = (tid >> 5) & 3, row = qt * 512 + (w >> 1) * 256 + (tid >> 7) * 64;
        tma_store_2d(&tm_ast, stg + (w >> 1) * 2 * BLK_BYTES + (w & 1) * 2048, h * 16, row + (w & 1) * 32);
        if (!(w & 1)) bulk_store(g_rem + (row >> 7) * 4096 + h * 128 + (row & 127), stg + (w >> 1) * 2 * BLK_BYTES + 4096, 256);
        bulk_commit();
        bulk_wait_all();
    }
}

constexpr uint32_t C_HALF = 73728;
constexpr uint32_t C_OFF_W = 147456, C_SLOT = 6144;
constexpr uint32_t C_OFF_CS = C_OFF_W + 12 * C_SLOT;
constexpr uint32_t C_OFF_BAR = C_OFF_W + 82944;
constexpr uint32_t C_OFF_ST = C_OFF_BAR + 512;
constexpr uint32_t C_SMEM = C_OFF_ST + 1024 + 512;

__device__ __forceinline__ uint32_t mean_frag(float m, int t) {
    const uint32_t hi = pack_bf16(m, m);
    return t == 0 ? hi : t == 1 ? pack_bf16(m - bf_lo(hi), 0.f) : 0u;
}
__device__ __forceinline__ void add_partial(float (&acc)[32], uint32_t src) {
#pragma unroll
    for (int i = 0; i < 4; i++) {
        const uint4 v = lds128(src + i * 512);
        acc[8 * i] += bf_lo(v.x); acc[8 * i + 1] += bf_hi(v.x); acc[8 * i + 2] += bf_lo(v.y); acc[8 * i + 3] += bf_hi(v.y);
        acc[8 * i + 4] += bf_lo(v.z); acc[8 * i + 5] += bf_hi(v.z); acc[8 * i + 6] += bf_lo(v.w); acc[8 * i + 7] += bf_hi(v.w);
    }
}

__global__ void __launch_bounds__(384, 1)
ffn_kernel(const __grid_constant__ CUtensorMap tm_attn, const __grid_constant__ CUtensorMap tm_w1, const __grid_constant__ CUtensorMap tm_w2,
           const __grid_constant__ CUtensorMap tm_out, const __nv_bfloat16* __restrict__ x, __nv_bfloat16* __restrict__ out) {
    extern __shared__ uint8_t smem_raw[];
    uint32_t spins = 0;
    const int tid = threadIdx.x, warp = __shfl_sync(~0u, tid >> 5, 0), lane = tid & 31;
    const uint32_t sb = (smem_u32(smem_raw) + 1023u) & ~1023u;
    const uint32_t bar_a = sb + C_OFF_BAR, bar_full = bar_a + 72, bar_wo = bar_full + 96, bar_cs = bar_wo + 8, bar_recv = bar_cs + 8;
    const uint32_t bar_hst = bar_recv + 16, bar_tfree = bar_hst + 8, bar_h = bar_tfree + 8, bar_g1 = bar_h + 64, bar_afree = bar_g1 + 8;
    const uint32_t bar_empty = bar_afree + 8, bar_pub = bar_empty + 96, bar_hpub = bar_pub + 64;
    const int rb = blockIdx.x & 15, e = blockIdx.x >> 4;
    const uint32_t rank = blockIdx.x & 1;
    const int wrb = blockIdx.x >> 3, wsl = blockIdx.x & 7;

    if (lane == 0) {
        if (warp == 9) {
            mbar_init(bar_wo, 1);
            fence_mbar_init();
            mbar_expect(bar_wo, 82944);
#pragma unroll 1
            for (int i = 0; i < 3; i++) bulk_load(sb + C_OFF_W + i * 27648, g_wo_img + wsl * 82944 + i * 27648, 27648, bar_wo);
        }
#pragma unroll
        for (int i = 0; i < 5; i++) {
            const int b = warp + 12 * i;
            if (b < 59 && b != 21) mbar_init(bar_a + 8 * b, b < 27 ? 1 : b < 37 ? 2 : b < 49 ? 4 : 8);
        }
        fence_mbar_init();
        mbar_expect(bar_a + 8 * (warp < 9 ? warp + 12 : warp), C_SLOT);
    }
    __syncwarp();
    if (tid == 320) { tma_prefetch_desc(&tm_attn); tma_prefetch_desc(&tm_w1); tma_prefetch_desc(&tm_w2); tma_prefetch_desc(&tm_out); }
    cluster_sync();

    if (warp >= 8) {
        asm volatile("setmaxnreg.dec.sync.aligned.u32 40;");
        if (warp == 8) {
            if (lane == 0) {
                pdl_wait();
#pragma unroll 1
                for (int kc = 0; kc < 8; kc++) {
                    mbar_expect(bar_a + 8 * kc, 16384);
                    tma_2d_mc(sb + kc * 16384 + rank * 8192, &tm_attn, kc * 64, wrb * 128 + rank * 64, bar_a + 8 * kc);
                    if (kc == 0) {
                        mbar_expect(bar_a + 64, 16384);
                        asm volatile("cp.async.bulk.shared::cluster.global.mbarrier::complete_tx::bytes.multicast::cluster [%0], [%1], %2, [%3], %4;"
                                     :: "r"(sb + 8 * 16384 + rank * 8192), "l"(g_rem + wrb * 4096 + rank * 2048), "r"(8192), "r"(bar_a + 64), "h"((uint16_t)3) : "memory");
                    }
                }
                uint32_t ph = 0;
#pragma unroll 1
                for (int rnd = 0; rnd < 18; rnd++) {
                    const int pass = rnd / 3, p = rnd - 9;
                    const int c0 = rnd < 9 ? e * 576 + pass * 192 : (p == 0 ? 8 : (e + p) & 7) * 64;
                    const int r0 = rnd < 9 ? (rnd - pass * 3) * 192 : e * 576;
                    if (rb < 12 && p + 3 >= 0 && p + 3 < 9)
                        asm volatile("cp.async.bulk.prefetch.tensor.2d.L2.global [%0, {%1, %2}];"
                                     :: "l"(&tm_w2), "r"((p + 3 == 0 ? 8 : (e + p + 3) & 7) * 64), "r"(e * 576 + rb * 48) : "memory");
#pragma unroll 1
                    for (int slot = rank; slot < 12; slot += 2) {
                        mbar_wait_trap(bar_empty + 8 * slot, ph);
                        if (rnd < 9) tma_3d_mc(sb + C_OFF_W + slot * C_SLOT, &tm_w1, c0, r0 + slot * 16, bar_full + 8 * slot);
                        else tma_2d_mc(sb + C_OFF_W + slot * C_SLOT, &tm_w2, c0, r0 + slot * 48, bar_full + 8 * slot);
                    }
                    ph ^= 1;
                }
            }
        } else if (warp == 11) {
            if (lane == 0) {
                mbar_wait_trap(bar_hpub, 0);
                flag_add(&g_flag_c[FLAG_H + wrb * 8 + wsl]);
                mbar_expect(bar_cs, 9216);
                bulk_load(sb + C_OFF_CS, g_cs1 + e * 9216, 9216, bar_cs);
                mbar_wait_trap(bar_hpub + 8, 0);
                flag_add(&g_flag_c[FLAG_HST + wrb]);
                flag_wait(&g_flag_c[FLAG_HST + rb], 8);
            }
            __syncwarp();
#pragma unroll 1
            for (int row = lane; row < 128; row += 32) {
                float2 v[8];
#pragma unroll
                for (int i = 0; i < 8; i++) v[i] = __ldcg(&g_hstat[i * SEQ + rb * 128 + row]);
                float sum = 0.f, m2 = 0.f;
#pragma unroll
                for (int i = 0; i < 8; i++) sum += v[i].x;
                const float mean = sum * (1.f / DM);
#pragma unroll
                for (int i = 0; i < 8; i++) { const float d = v[i].x * (1.f / 72) - mean; m2 += v[i].y + 72.f * d * d; }
                sts64f(sb + C_OFF_ST + row * 8, mean, rsqrtf(m2 * (1.f / DM) + LN_EPS));
            }
            __syncwarp();
            if (lane == 0) mbar_arrive(bar_hst);
            mbar_wait_trap(bar_g1, 0);
#pragma unroll 1
            for (int i = 0; i < 4; i++) {
                const uint4 v = lds128(sb + (e >> 2) * C_HALF + (64 + 2 * i + (lane >> 4)) * 1024 + (e & 3) * 256 + (lane & 15) * 16);
                sts128(sb + C_OFF_CS + i * 512 + lane * 16, v.x, v.y, v.z, v.w);
            }
            __syncwarp();
            const int r = lane >> 2, t = lane & 3, row = rb * 128 + e * 16 + r;
            const float rs0 = lds64f(sb + C_OFF_ST + (e * 16 + r) * 8).y, rs1 = lds64f(sb + C_OFF_ST + (e * 16 + r + 8) * 8).y;
            const uint32_t tmp = sb + ((e + 2) & 7) * 8192;
            if (lane < 8) flag_wait(&g_flag_c[FLAG_PART + (rb * 9 + 8) * 8 + lane], 1);
            __syncwarp();
            if (lane == 0) {
                mbar_expect(bar_cs, 16384);
#pragma unroll 1
                for (int c = 0; c < 8; c++)
                    bulk_load(tmp + (c >> 2) * C_HALF + (c & 3) * 2048, g_part + (size_t)((rb * 9 + 8) * 8 + c) * 16384 + e * 2048, 2048, bar_cs);
            }
            mbar_wait_trap(bar_cs, 1);
#pragma unroll 1
            for (int i = 0; i < 8; i++) {
                const uint32_t h0 = lds32(sb + C_OFF_CS + i * 256 + lane * 4), h1 = lds32(sb + C_OFF_CS + i * 256 + 128 + lane * 4);
                float a0 = 0.f, a1 = 0.f, a2 = 0.f, a3 = 0.f;
#pragma unroll
                for (int c = 0; c < 8; c++) {
                    const float2 v = lds64f(tmp + (c >> 2) * C_HALF + (c & 3) * 2048 + (i >> 1) * 512 + lane * 16 + (i & 1) * 8);
                    a0 += bf_lo(__float_as_uint(v.x)); a1 += bf_hi(__float_as_uint(v.x)); a2 += bf_lo(__float_as_uint(v.y)); a3 += bf_hi(__float_as_uint(v.y));
                }
                uint32_t* po = (uint32_t*)out + ((size_t)row * DM + 512 + 8 * i) / 2 + t;
                po[0] = pack_bf16(bf_lo(h0) + rs0 * a0, bf_hi(h0) + rs0 * a1);
                po[4 * DM] = pack_bf16(bf_lo(h1) + rs1 * a2, bf_hi(h1) + rs1 * a3);
            }
            fence_async_smem();
            __syncwarp();
            if (lane == 0) { mbar_arrive(bar_tfree); }
        } else {
            const int w = warp - 9;
            mbar_wait_trap(bar_afree, 0);
#pragma unroll 1
            for (uint32_t sl = 0, it = 0; sl < 8; it++) {
                const uint32_t m = flag_poll(&g_flag_c[FLAG_H + rb * 8 + (lane & 7)], lane < 8, 1);
#pragma unroll 1
                for (; sl < 8 && ((m >> sl) & 1); sl++) {
                    if (lane == 0) {
                        if (sl >= 2) mbar_wait_trap(bar_h + 8 * (sl - 2), 0);
                        flag_acquire();
                        mbar_expect(bar_h + 8 * sl, 9216);
                        bulk_load(sb + w * C_HALF + sl * 9216, g_h + rb * 147456 + w * C_HALF + sl * 9216, 9216, bar_h + 8 * sl);
                    }
                    __syncwarp();
                }
                if (it > SPIN_LIMIT) __trap();
            }
            if (w == 0) {
                if (lane == 0) {
#pragma unroll 1
                    for (int p = 0; p < 8; p++) {
                        mbar_wait_trap(bar_pub + 8 * p, 0);
                        flag_add(&g_flag_c[FLAG_PART + (rb * 9 + (p == 0 ? 8 : (e + p) & 7)) * 8 + e]);
                    }
                }
            } else {
                mbar_wait_trap(bar_g1, 0);
                if (lane == 0) { mbar_expect(bar_recv, 5 * 16384); mbar_expect(bar_wo, 16384); mbar_expect(bar_recv + 8, 16384); }
#pragma unroll 1
                for (uint32_t p = 1, it = 0; p < 8; it++) {
                    const uint32_t m = flag_poll(&g_flag_c[FLAG_PART + (rb * 9 + e) * 8 + ((e - lane) & 7)], lane < 8, 1);
#pragma unroll 1
                    for (; p < 8 && ((m >> p) & 1); p++) {
                        if (lane == 0) {
                            const int c = (e - p) & 7;
                            const uint8_t* src = g_part + (size_t)((rb * 9 + e) * 8 + c) * 16384;
                            if (p == 6) mbar_wait_trap(bar_tfree, 0);
                            flag_acquire();
                            const uint32_t dst = sb + (p == 7 ? 8 : c) * 8192;
                            const uint32_t b = p < 6 ? bar_recv : p == 6 ? bar_wo : bar_recv + 8;
                            bulk_load(dst, src, 8192, b);
                            bulk_load(dst + C_HALF, src + 8192, 8192, b);
                        }
                        __syncwarp();
                    }
                    if (it > SPIN_LIMIT) __trap();
                }
            }
        }
    } else {
        asm volatile("setmaxnreg.inc.sync.aligned.u32 232;");
        const int wg = warp >> 2, t = lane & 3, r = lane >> 2;
        const uint32_t rel = mapa(bar_empty, warp & 1);
        const bool rel_even = (tid & 127) == 0, rel_odd = (tid & 127) == 32, arm = tid == 64;
        {
            const uint32_t* px = (const uint32_t*)(x + (size_t)(wrb * 128 + warp * 16 + r) * DM + wsl * 72) + t;
            uint32_t xr[18];
#pragma unroll
            for (int j = 0; j < 9; j++) { xr[2 * j] = __ldg(px + 4 * j); xr[2 * j + 1] = __ldg(px + 8 * (DM / 2) + 4 * j); }
            float acc[36];
#pragma unroll
            for (int i = 0; i < 36; i++) acc[i] = 0.f;
            fence_regs(acc);
            const uint32_t a_lo = desc_addr(sb + wg * 8192) | (1u << 16);
            const uint32_t b_lo = desc_addr(sb + C_OFF_W) | ((128 >> 4) << 16);
            mbar_wait(bar_wo, 0, spins);
            auto wo_chunks = [&](int k0, int k1) {
#pragma unroll 1
                for (int kc = k0; kc < k1; kc++) {
                    mbar_wait(bar_a + 8 * kc, 0, spins);
                    wg_fence();
#pragma unroll
                    for (int j = 0; j < 4; j++) mma_ss_n72(acc, a_lo + kc * 1024 + j * 2, HI_SW128, b_lo + (kc * 4 + j) * 144, 256 >> 4, 1);
                    wg_commit();
                }
            };
            wo_chunks(0, 2);
            mbar_wait(bar_a + 64, 0, spins);
            uint32_t ar[16];
#pragma unroll
            for (int i = 0; i < 16; i++) ar[i] = lds32(sb + 8 * 16384 + ((i >> 1) * 4 + t) * 512 + wg * 256 + (((warp & 3) * 16 + (i & 1) * 8 + t * 8 + r) & 63) * 4);
            wg_fence();
#pragma unroll
            for (int j = 0; j < 4; j++) mma_rs_n72(acc, ar[4 * j], ar[4 * j + 1], ar[4 * j + 2], ar[4 * j + 3], b_lo + (32 + j) * 144, 256 >> 4);
            wg_commit();
            wo_chunks(2, 8);
            wg_wait<0>();
            fence_regs(acc);
            if (rel_even || rel_odd) {
#pragma unroll
                for (int i = 0; i < 6; i++) mbar_arrive_cluster(rel + 8 * (warp & 1) + 16 * i);
            }
            if (rel_even) mbar_arrive(bar_afree);
            uint32_t hw[18];
            uint32_t* ph = (uint32_t*)(g_h + wrb * 147456 + wg * C_HALF + wsl * 9216 + (warp & 3) * 256) + lane;
#pragma unroll
            for (int j = 0; j < 9; j++) {
                hw[2 * j] = pack_bf16(acc[4 * j] + bf_lo(xr[2 * j]), acc[4 * j + 1] + bf_hi(xr[2 * j]));
                hw[2 * j + 1] = pack_bf16(acc[4 * j + 2] + bf_lo(xr[2 * j + 1]), acc[4 * j + 3] + bf_hi(xr[2 * j + 1]));
                ph[256 * j] = hw[2 * j]; ph[256 * j + 32] = hw[2 * j + 1];
            }
            __syncwarp();
            if (lane == 0) mbar_arrive(bar_hpub);
            fence_regs(hw);
            float s0 = 0.f, s1 = 0.f;
#pragma unroll
            for (int j = 0; j < 9; j++) { s0 += bf_lo(hw[2 * j]) + bf_hi(hw[2 * j]); s1 += bf_lo(hw[2 * j + 1]) + bf_hi(hw[2 * j + 1]); }
            s0 += __shfl_xor_sync(~0u, s0, 1); s0 += __shfl_xor_sync(~0u, s0, 2);
            s1 += __shfl_xor_sync(~0u, s1, 1); s1 += __shfl_xor_sync(~0u, s1, 2);
            const float m0 = s0 * (1.f / 72), m1 = s1 * (1.f / 72);
            float q0 = 0.f, q1 = 0.f;
#pragma unroll
            for (int j = 0; j < 9; j++) {
                const float a = bf_lo(hw[2 * j]) - m0, b = bf_hi(hw[2 * j]) - m0, c = bf_lo(hw[2 * j + 1]) - m1, d = bf_hi(hw[2 * j + 1]) - m1;
                q0 += a * a + b * b; q1 += c * c + d * d;
            }
            q0 += __shfl_xor_sync(~0u, q0, 1); q0 += __shfl_xor_sync(~0u, q0, 2);
            q1 += __shfl_xor_sync(~0u, q1, 1); q1 += __shfl_xor_sync(~0u, q1, 2);
            if (t == 0) {
                float2* ps = g_hstat + wsl * SEQ + wrb * 128 + warp * 16 + r;
                ps[0] = make_float2(s0, q0); ps[8] = make_float2(s1, q1);
            }
            __syncwarp();
            if (lane == 0) mbar_arrive(bar_hpub + 8);
        }
        uint32_t hreg[128];
        const uint32_t s_hx = sb + wg * C_HALF + ((e + 1) & 7) * 8192;
        float rstd0, rstd1;
        uint32_t mf0, mf1;
        uint32_t ph = 0;
        const uint32_t a_lo = desc_addr(sb + wg * C_HALF) | ((1024 >> 4) << 16);
        const uint32_t b1_lo = desc_addr(sb + C_OFF_W) | ((2048 >> 4) << 16);
        uint32_t slot = 0, hnext = 0;
        auto g1_steps = [&](float (&acc)[96], int pass, int n, bool release_prev) {
#pragma unroll
            for (int j = 0; j < 2; j++) {
                if (pass == 0 && 2 * (n + j) + 1 >= 9 * (int)hnext) {
                    mbar_wait(bar_h + 8 * hnext, 0, spins);
                    hnext++;
                }
                mbar_wait(bar_full + 8 * (slot + j), ph, spins);
                wg_fence();
                mma_ss_n192(acc, a_lo + (n + j) * 128, 128 >> 4, b1_lo + (slot + j) * (C_SLOT >> 4), HI_SW128, (uint32_t)(n + j));
                wg_commit();
                if (arm) mbar_expect(bar_full + 8 * (slot + j), C_SLOT);
                wg_wait<1>();
                if (j == 1 ? rel_even : (rel_odd && release_prev)) mbar_arrive_cluster(rel + 8 * (j == 1 ? slot : slot == 0 ? 11 : slot - 1));
            }
            slot += 2;
            if (slot == 12) { slot = 0; ph ^= 1; }
        };
        auto g1_mean = [&](float (&acc)[96], int pass) {
            wg_fence();
            mma_rs_n192(acc, mf0, mf1, 0u, 0u, desc_addr(sb + C_OFF_CS) + pass * 192, 128 >> 4);
            wg_commit();
            wg_wait<1>();
            if (rel_odd) mbar_arrive_cluster(rel + 8 * 11);
        };
        auto g1_pack = [&](float (&acc)[96], auto pass_tag) {
            constexpr int pass = decltype(pass_tag)::value;
            fence_regs(acc);
#pragma unroll
            for (int j = 0; j < 48; j++) {
                const uint32_t w = pack_bf16_relu(acc[2 * j], acc[2 * j + 1]);
                if (pass * 48 + j < 128) hreg[(pass * 48 + j) & 127] = w;
                else sts32(s_hx + ((j - 32) >> 1) * 1024 + (warp & 3) * 256 + (j & 1) * 128 + lane * 4, w);
            }
        };
        {
            float acca[96], accb[96];
#pragma unroll 1
            for (int n = 0; n < 36; n += 2) g1_steps(acca, 0, n, n > 0);
            mbar_wait(bar_hst, 0, spins);
            const float2 s0 = lds64f(sb + C_OFF_ST + (warp * 16 + r) * 8), s1 = lds64f(sb + C_OFF_ST + (warp * 16 + r + 8) * 8);
            rstd0 = s0.y; rstd1 = s1.y;
            mf0 = mean_frag(s0.x, t); mf1 = mean_frag(s1.x, t);
            mbar_wait(bar_cs, 0, spins);
            g1_mean(acca, 0);
            g1_steps(accb, 1, 0, false);
            g1_pack(acca, std::integral_constant<int, 0>());
#pragma unroll 1
            for (int n = 2; n < 36; n += 2) g1_steps(accb, 1, n, true);
            g1_mean(accb, 1);
            wg_wait<0>();
            g1_pack(accb, std::integral_constant<int, 1>());
        }
        {
            float acc[96];
#pragma unroll 1
            for (int n = 0; n < 36; n += 2) g1_steps(acc, 2, n, n > 0);
            g1_mean(acc, 2);
            wg_wait<0>();
            if (rel_even) mbar_arrive(bar_g1);
            g1_pack(acc, std::integral_constant<int, 2>());
        }
        fence_async_smem();
        nbar_sync(2 + wg, 128);
        fence_regs(hreg);
        const uint32_t b_lo = desc_addr(sb + C_OFF_W) | (1u << 16);
        const uint32_t stg = sb + wg * C_HALF + 65536;
        const uint32_t hx_lo = desc_addr(s_hx) | ((1024 >> 4) << 16);
        float acc0[32], acc1[32];
        auto send = [&](const float (&a)[32], int p) {
            uint4* dst = (uint4*)(g_part + (size_t)((rb * 9 + (p == 0 ? 8 : (e + p) & 7)) * 8 + e) * 16384 + warp * 2048) + lane;
#pragma unroll
            for (int i = 0; i < 4; i++)
                dst[i * 32] = make_uint4(pack_bf16(a[8 * i], a[8 * i + 1]), pack_bf16(a[8 * i + 2], a[8 * i + 3]),
                                         pack_bf16(a[8 * i + 4], a[8 * i + 5]), pack_bf16(a[8 * i + 6], a[8 * i + 7]));
            __syncwarp();
            if (lane == 0) mbar_arrive(bar_pub + 8 * p);
        };
        auto gemm2_pass = [&](auto kind_tag, int p, float (&acc)[32], float (&prev)[32]) {
            constexpr int KIND = decltype(kind_tag)::value;
            constexpr bool LAST = KIND == 2, CHAIN = KIND == 1;
#pragma unroll
            for (int st = 0; st < 12; st++) {
                mbar_wait(bar_full + 8 * st, KIND != 1, spins);
                wg_fence();
#pragma unroll
                for (int j = 0; j < 3; j++) {
                    const int kk = st * 3 + j;
                    const uint32_t bl = b_lo + st * (C_SLOT >> 4) + j * 128;
                    if (kk < 32) mma_rs_n64(acc, hreg[(4 * kk) & 127], hreg[(4 * kk + 1) & 127], hreg[(4 * kk + 2) & 127], hreg[(4 * kk + 3) & 127], bl, HI_SW128, kk > 0 ? 1u : 0u);
                    else mma_ss_n64(acc, hx_lo + (kk - 32) * 128, 128 >> 4, bl, HI_SW128);
                }
                wg_commit();
                if (!LAST && arm) mbar_expect(bar_full + 8 * st, C_SLOT);
                if (LAST && st >= 4 && st < 11 && st != 9) {
                    if (st == 4) {
                        mbar_wait(bar_recv, 0, spins);
#pragma unroll
                        for (int i = 0; i < 32; i++) prev[i] = 0.f;
                    }
                    if (st == 10) mbar_wait(bar_wo, 1, spins);
                    add_partial(prev, sb + wg * C_HALF + ((e + (st == 10 ? 2 : 3 - st)) & 7) * 8192 + (warp & 3) * 2048 + lane * 16);
                }
                if (st >= 1 || CHAIN) wg_wait<1>();
                if ((st >= 1 ? !LAST : CHAIN) && ((st & 1) ? rel_even : rel_odd)) mbar_arrive_cluster(rel + 8 * ((st + 11) % 12));
                if (st == 0 && (EARLY7 ? !LAST : true) && (KIND > 0 || p > 0)) {
                    fence_regs(prev);
                    send(prev, p - 1);
                }
            }
        };
#pragma unroll 1
        for (int p = 0; p < 8; p += 2) {
            gemm2_pass(std::integral_constant<int, 0>(), p, acc0, acc1);
            gemm2_pass(std::integral_constant<int, 1>(), p + 1, acc1, acc0);
            wg_wait<0>();
            fence_regs(acc1);
            if (rel_odd) mbar_arrive_cluster(rel + 8 * 11);
        }
        if (EARLY7) send(acc1, 7);
        gemm2_pass(std::integral_constant<int, 2>(), 8, acc0, acc1);
        float (&acc)[32] = acc0, (&sum)[32] = acc1;
        const uint32_t hb = sb + wg * C_HALF + e * 8192 + (warp & 3) * 256 + lane * 4;
        uint32_t hv[16];
#pragma unroll
        for (int j = 0; j < 8; j++) { hv[2 * j] = lds32(hb + j * 1024); hv[2 * j + 1] = lds32(hb + j * 1024 + 128); }
        mbar_wait(bar_recv + 8, 0, spins);
        add_partial(sum, stg + (warp & 3) * 2048 + lane * 16);
#pragma unroll
        for (int j = 0; j < 8; j++) {
            sum[4 * j] = fmaf(sum[4 * j], rstd0, bf_lo(hv[2 * j])); sum[4 * j + 1] = fmaf(sum[4 * j + 1], rstd0, bf_hi(hv[2 * j]));
            sum[4 * j + 2] = fmaf(sum[4 * j + 2], rstd1, bf_lo(hv[2 * j + 1])); sum[4 * j + 3] = fmaf(sum[4 * j + 3], rstd1, bf_hi(hv[2 * j + 1]));
        }
        fence_regs(sum);
        const uint32_t ob = stg + (warp & 3) * 2048 + (lane & 15) * 128;
        wg_wait<0>();
        fence_regs(acc);
#pragma unroll
        for (int j = 0; j < 8; j += 2)
            asm volatile("stmatrix.sync.aligned.m8n8.x4.shared.b16 [%0], {%1, %2, %3, %4};"
                         :: "r"(ob + (((j + (lane >> 4)) ^ (lane & 7)) << 4)),
                            "r"(pack_bf16(fmaf(acc[4 * j], rstd0, sum[4 * j]), fmaf(acc[4 * j + 1], rstd0, sum[4 * j + 1]))),
                            "r"(pack_bf16(fmaf(acc[4 * j + 2], rstd1, sum[4 * j + 2]), fmaf(acc[4 * j + 3], rstd1, sum[4 * j + 3]))),
                            "r"(pack_bf16(fmaf(acc[4 * j + 4], rstd0, sum[4 * j + 4]), fmaf(acc[4 * j + 5], rstd0, sum[4 * j + 5]))),
                            "r"(pack_bf16(fmaf(acc[4 * j + 6], rstd1, sum[4 * j + 6]), fmaf(acc[4 * j + 7], rstd1, sum[4 * j + 7]))) : "memory");
        fence_async_smem();
        __syncwarp();
        if (lane == 0) {
            tma_store_2d(&tm_out, stg + (warp & 3) * 2048, e * 64, rb * 128 + warp * 16);
            bulk_commit();
            bulk_wait_all();
        }
    }
}

typedef CUresult (*EncodeFn)(CUtensorMap*, CUtensorMapDataType, cuuint32_t, void*, const cuuint64_t*, const cuuint64_t*,
                             const cuuint32_t*, const cuuint32_t*, CUtensorMapInterleave, CUtensorMapSwizzle,
                             CUtensorMapL2promotion, CUtensorMapFloatOOBfill);

void make_map(EncodeFn enc, CUtensorMap* m, const void* ptr, int cols, int rows, int box_c, int box_r, int chunks, CUtensorMapSwizzle sw) {
    const cuuint64_t dims[3] = {(cuuint64_t)cols, (cuuint64_t)rows, (cuuint64_t)chunks};
    const cuuint64_t strides[2] = {(cuuint64_t)cols * 2, (cuuint64_t)box_c * 2};
    const cuuint32_t box[3] = {(cuuint32_t)box_c, (cuuint32_t)box_r, (cuuint32_t)chunks};
    const cuuint32_t es[3] = {1, 1, 1};
    enc(m, CU_TENSOR_MAP_DATA_TYPE_BFLOAT16, chunks > 1 ? 3 : 2, (void*)ptr, dims, strides, box, es, CU_TENSOR_MAP_INTERLEAVE_NONE, sw,
        CU_TENSOR_MAP_L2_PROMOTION_NONE, CU_TENSOR_MAP_FLOAT_OOB_FILL_NONE);
}

}

extern "C" void kernel_launch(void* const* d_in, const int* in_sizes, int n_in, void* d_out, int out_size) {
    const __nv_bfloat16* x = (const __nv_bfloat16*)d_in[0];
    const __nv_bfloat16* wqkv = (const __nv_bfloat16*)d_in[1];
    const __nv_bfloat16* wo = (const __nv_bfloat16*)d_in[2];
    const __nv_bfloat16* w1 = (const __nv_bfloat16*)d_in[4];
    const __nv_bfloat16* w2 = (const __nv_bfloat16*)d_in[5];

    void* fn = nullptr;
    cudaDriverEntryPointQueryResult qr;
    cudaGetDriverEntryPoint("cuTensorMapEncodeTiled", &fn, cudaEnableDefault, &qr);
    EncodeFn enc = (EncodeFn)fn;
    void* p_attn = nullptr;
    cudaGetSymbolAddress(&p_attn, g_attn);
    CUtensorMap tm_x, tm_wqkv, tm_wo, tm_wo2, tm_ast, tm_attn, tm_w1, tm_w2, tm_out;
    make_map(enc, &tm_x, x, DM, SEQ, 64, 128, 1, CU_TENSOR_MAP_SWIZZLE_128B);
    make_map(enc, &tm_wqkv, wqkv, 1728, DM, 32, 16, 7, CU_TENSOR_MAP_SWIZZLE_64B);
    {
        const cuuint64_t dims[4] = {DM, 16, 9, 32}, strides[3] = {DM * 2, 16, 18 * DM * 2};
        const cuuint32_t box[4] = {8, 16, 9, 16}, es[5] = {1, 1, 1, 1, 1};
        enc(&tm_wo, CU_TENSOR_MAP_DATA_TYPE_BFLOAT16, 4, (void*)wo, dims, strides, box, es, CU_TENSOR_MAP_INTERLEAVE_NONE,
            CU_TENSOR_MAP_SWIZZLE_NONE, CU_TENSOR_MAP_L2_PROMOTION_NONE, CU_TENSOR_MAP_FLOAT_OOB_FILL_NONE);
        const cuuint64_t dims2[5] = {DM, 2, 8, 9, 4}, strides2[4] = {DM * 2, 18 * DM * 2, 16, 144 * DM * 2};
        const cuuint32_t box2[5] = {8, 2, 8, 9, 4};
        enc(&tm_wo2, CU_TENSOR_MAP_DATA_TYPE_BFLOAT16, 5, (void*)(wo + 16 * DM), dims2, strides2, box2, es, CU_TENSOR_MAP_INTERLEAVE_NONE,
            CU_TENSOR_MAP_SWIZZLE_NONE, CU_TENSOR_MAP_L2_PROMOTION_NONE, CU_TENSOR_MAP_FLOAT_OOB_FILL_NONE);
    }
    make_map(enc, &tm_attn, p_attn, 512, SEQ, 64, 64, 1, CU_TENSOR_MAP_SWIZZLE_128B);
    make_map(enc, &tm_ast, p_attn, 512, SEQ, 16, 32, 1, CU_TENSOR_MAP_SWIZZLE_NONE);
    make_map(enc, &tm_w1, w1, FF, DM, 64, 16, 3, CU_TENSOR_MAP_SWIZZLE_128B);
    make_map(enc, &tm_w2, w2, DM, FF, 64, 48, 1, CU_TENSOR_MAP_SWIZZLE_128B);
    make_map(enc, &tm_out, d_out, DM, SEQ, 64, 16, 1, CU_TENSOR_MAP_SWIZZLE_128B);

    cudaFuncSetAttribute(qkv_kernel, cudaFuncAttributeMaxDynamicSharedMemorySize, A_SMEM);
    cudaFuncSetAttribute(attn_kernel, cudaFuncAttributeMaxDynamicSharedMemorySize, B_SMEM);
    cudaFuncSetAttribute(ffn_kernel, cudaFuncAttributeMaxDynamicSharedMemorySize, C_SMEM);

    cudaLaunchAttribute at[2];
    at[0].id = cudaLaunchAttributeClusterDimension;
    at[0].val.clusterDim.x = 2; at[0].val.clusterDim.y = 1; at[0].val.clusterDim.z = 1;
    at[1].id = cudaLaunchAttributeProgrammaticStreamSerialization;
    at[1].val.programmaticStreamSerializationAllowed = 1;

    cudaLaunchConfig_t cfg = {};
    cfg.stream = cudaStreamPerThread;
    cfg.gridDim = 128; cfg.blockDim = 384; cfg.dynamicSmemBytes = A_SMEM; cfg.attrs = at; cfg.numAttrs = 1;
    cudaLaunchKernelEx(&cfg, qkv_kernel, tm_x, tm_wqkv, x);
    cfg.gridDim = 132; cfg.blockDim = 512; cfg.dynamicSmemBytes = B_SMEM; cfg.attrs = at + 1; cfg.numAttrs = 1;
    cudaLaunchKernelEx(&cfg, attn_kernel, tm_wo, tm_wo2, tm_ast, w1);
    cfg.gridDim = 128; cfg.blockDim = 384; cfg.dynamicSmemBytes = C_SMEM; cfg.attrs = at; cfg.numAttrs = 2;
    cudaLaunchKernelEx(&cfg, ffn_kernel, tm_attn, tm_w1, tm_w2, tm_out, x, (__nv_bfloat16*)d_out);
}
```
